```python
import torch

def _softmax(x, axis=-1):
    return torch.softmax(x, dim=axis)
def _gelu(x):
    return torch.nn.functional.gelu(x, approximate="tanh")
def _silu(x):
    return torch.nn.functional.silu(x)
def _sigmoid(x):
    return torch.sigmoid(x)
def _layernorm(x, axis=-1, eps=1e-5):
    m = x.mean(dim=axis, keepdim=True)
    v = x.var(dim=axis, keepdim=True, unbiased=False)
    return (x - m) / torch.sqrt(v + eps)
def _scatter_add(tgt, idx, src, axis=0):
    return tgt.clone().index_add_(axis, idx, src)
def _segment_sum(src, seg, n):
    out = torch.zeros((n,) + src.shape[1:], dtype=src.dtype)
    return out.index_add_(0, seg, src)
def _pad(x, pw):
    flat = tuple(v for pair in reversed(pw) for v in pair)
    return torch.nn.functional.pad(x, flat)

kernel_name = 'standalone__sliding_block_cached__decode'

def setup_inputs():

    _w = (lambda a: (lambda t: t.to(torch.bfloat16) if t.is_floating_point() else t)(torch.as_tensor(a)))
    B, Sq, D = 2, 1, 576
    Hq, Hkv, Sk, Dh = 32, 16, 32768, 128
    assert Hq % Hkv == 0, (Hq, Hkv)
    return {
        "x": _w((lambda *s: torch.randn(*s, dtype=torch.bfloat16) * 0.8)(B, Sq, D)),
        "k_cache": _w((lambda *s: torch.randn(*s, dtype=torch.bfloat16) * 0.8)(B, Hkv, Sk, Dh)),
        "v_cache": _w((lambda *s: torch.randn(*s, dtype=torch.bfloat16) * 0.05)(B, Hkv, Sk, Dh)),
        "wq": _w((lambda *s: torch.randn(*s, dtype=torch.bfloat16) * 0.8)(D, Hq * Dh) * (D ** -0.5)),
        "wo": _w((lambda *s: torch.randn(*s, dtype=torch.bfloat16) * 0.05)(Hq * Dh, D) * ((Hq * Dh) ** -0.5)),
    }

def reference(x, k_cache, v_cache, wq, wo):
    B, Sq, D = x.shape
    Hq, Dh = 32, 128
    Hkv, Sk = k_cache.shape[1], k_cache.shape[2]
    W = min(4096, max(256, Sk // 4))
    rep = Hq // Hkv
    q = (lambda x, *d: x.permute(*d))((x @ wq).reshape(B, Sq, Hq, Dh), 0, 2, 1, 3)
    k = (lambda x, n, axis: torch.repeat_interleave(x, n, dim=axis))(k_cache[:, :, Sk - W:, :], rep, axis=1)
    v = (lambda x, n, axis: torch.repeat_interleave(x, n, dim=axis))(v_cache[:, :, Sk - W:, :], rep, axis=1)
    scores = torch.einsum("bhqd,bhkd->bhqk", q, k) * (Dh ** -0.5)
    p = _softmax(scores, axis=-1)
    o = torch.einsum("bhqk,bhkd->bhqd", p, v)
    return (lambda x, *d: x.permute(*d))(o, 0, 2, 1, 3).reshape(B, Sq, Hq * Dh) @ wo
```

```cpp
#include <cuda_runtime.h>
#include <cuda.h>
#include <cuda_bf16.h>
#include <stdint.h>

namespace {

constexpr int kD = 576, kSK = 32768, kDH = 128, kW = 4096;
constexpr int kNCTA = 128;
constexpr int kConsumerWarps = 8;
#define K_BAL 1
#define K_BAL_BIAS 200
#define K_BAL_HI1 64
#define K_BAL_HI2 192
#define K_BAL_HI3 100000
#define K_BAL_LO2 100000
#define K_WO_GATE 0
#define K_BAL_UNTIL 99
#define K_BAL_LO 96
constexpr int kThreads = 352;
constexpr int kTileBytes = 16384;
constexpr int kNSlot = 12;
#define K_INFLIGHT 4
#define K_START 3
#define K_NWO 4
#define K_END_AT 28
#define K_END_WIN 3
constexpr int kInflight = K_INFLIGHT;
constexpr int kStart = K_START;
#define K_WIN0 3
constexpr int kWin0 = K_WIN0;
constexpr int kNWo = K_NWO;
constexpr int kWoRows = 256 / kNWo;
constexpr int kTiles = 16;
constexpr int kWoCols = 72;
constexpr int kWoBytes = 256 * kWoCols * 2;
constexpr int kWoSlot = 8;

constexpr int kOffRing = 0;
constexpr int kOffRed = kOffRing + kNSlot * kTileBytes;
constexpr int kOffP = kOffRed + 8 * 2 * 2 * 128 * 4;
constexpr int kOffQ = kOffP + 8 * 512;
constexpr int kOffO = kOffQ + 512;
constexpr int kOffML = kOffO + 1024;
constexpr int kOffPart = kOffML + 16 * 2 * 8 + 16;
constexpr int kOffX = kOffPart + 8 * 2 * 80 * 4;
constexpr int kOffMon = kOffX + 1160;
constexpr int kOffBar = kOffX + 1168;
constexpr int kItems = 2 * kTiles + kNWo;
constexpr int kNumBars = kItems + 2 * kTiles + 2;
constexpr int kSmemBytes = kOffBar + kNumBars * 8;

constexpr int kTsBytes = 0;
constexpr float kScaleLog2 = 0.08838834764831845f * 1.4426950408889634f;
constexpr uint32_t kSpinLimit = 1u << 22;

struct Scratch {
    float q[16][2][2][256];
    float c[16][8][256];
    float r[8][16][144];
    unsigned long long ml[32][4][4];
    unsigned epoch;
    unsigned pad[31];
    unsigned landed;
};
__device__ Scratch g_scratch;

#define TS(i) do { } while (0)

#define SPIN_FAIL(id) __trap()
__device__ __forceinline__ uint32_t smem_u32(const void* p) { return (uint32_t)__cvta_generic_to_shared(p); }
__device__ __forceinline__ void mbar_init(uint32_t bar, uint32_t cnt) {
    asm volatile("mbarrier.init.shared::cta.b64 [%0], %1;" ::"r"(bar), "r"(cnt) : "memory");
}
__device__ __forceinline__ void mbar_expect_tx(uint32_t bar, uint32_t bytes) {
    asm volatile("mbarrier.arrive.expect_tx.shared::cta.b64 _, [%0], %1;" ::"r"(bar), "r"(bytes) : "memory");
}
__device__ __forceinline__ void mbar_arrive(uint32_t bar) {
    asm volatile("mbarrier.arrive.shared::cta.b64 _, [%0];" ::"r"(bar) : "memory");
}
__device__ __forceinline__ void mbar_wait(uint32_t bar, uint32_t parity, int id = 0) {
    uint32_t done, it = 0;
    do {
        asm volatile(
            "{\n.reg .pred p;\n"
            "mbarrier.try_wait.parity.shared::cta.b64 p, [%1], %2;\n"
            "selp.u32 %0, 1, 0, p;\n}"
            : "=r"(done) : "r"(bar), "r"(parity) : "memory");
        if (++it > kSpinLimit) SPIN_FAIL(id);
    } while (!done);
}
__device__ __forceinline__ bool mbar_test(uint32_t bar, uint32_t parity) {
    uint32_t done;
    asm volatile(
        "{\n.reg .pred p;\n"
        "mbarrier.test_wait.parity.shared::cta.b64 p, [%1], %2;\n"
        "selp.u32 %0, 1, 0, p;\n}"
        : "=r"(done) : "r"(bar), "r"(parity) : "memory");
    return done != 0;
}
__device__ __forceinline__ void bulk_g2s(uint32_t dst, const void* src, uint32_t bytes, uint32_t bar, uint64_t pol) {
    asm volatile(
        "cp.async.bulk.shared::cluster.global.mbarrier::complete_tx::bytes.L2::cache_hint [%0], [%1], %2, [%3], %4;"
        ::"r"(dst), "l"(src), "r"(bytes), "r"(bar), "l"(pol) : "memory");
}
__device__ __forceinline__ void tma_2d(uint32_t dst, const CUtensorMap* map, int c0, int c1, uint32_t bar, uint64_t pol) {
    asm volatile(
        "cp.async.bulk.tensor.2d.shared::cluster.global.mbarrier::complete_tx::bytes.L2::cache_hint"
        " [%0], [%1, {%3, %4}], [%2], %5;"
        ::"r"(dst), "l"(map), "r"(bar), "r"(c0), "r"(c1), "l"(pol) : "memory");
}
__device__ __forceinline__ uint4 ldsm_x4_trans(uint32_t addr) {
    uint4 v;
    asm volatile("ldmatrix.sync.aligned.m8n8.x4.trans.shared.b16 {%0,%1,%2,%3}, [%4];"
                 : "=r"(v.x), "=r"(v.y), "=r"(v.z), "=r"(v.w) : "r"(addr) : "memory");
    return v;
}
__device__ __forceinline__ uint4 lds128(uint32_t addr) {
    uint4 v;
    asm volatile("ld.shared.v4.u32 {%0,%1,%2,%3}, [%4];" : "=r"(v.x), "=r"(v.y), "=r"(v.z), "=r"(v.w) : "r"(addr));
    return v;
}
__device__ __forceinline__ void mma_bf16(float (&c)[4], uint32_t a0, uint32_t a1, uint32_t a2, uint32_t a3,
                                         uint32_t b0, uint32_t b1) {
    asm volatile(
        "mma.sync.aligned.m16n8k16.row.col.f32.bf16.bf16.f32 {%0,%1,%2,%3}, {%4,%5,%6,%7}, {%8,%9}, {%0,%1,%2,%3};"
        : "+f"(c[0]), "+f"(c[1]), "+f"(c[2]), "+f"(c[3])
        : "r"(a0), "r"(a1), "r"(a2), "r"(a3), "r"(b0), "r"(b1));
}
__device__ __forceinline__ void mma_bf16_z(float (&c)[4], uint32_t a0, uint32_t a1, uint32_t a2, uint32_t a3,
                                           uint32_t b0, uint32_t b1) {
    asm volatile(
        "mma.sync.aligned.m16n8k16.row.col.f32.bf16.bf16.f32 {%0,%1,%2,%3}, {%4,%5,%6,%7}, {%8,%9}, {%10,%10,%10,%10};"
        : "=f"(c[0]), "=f"(c[1]), "=f"(c[2]), "=f"(c[3])
        : "r"(a0), "r"(a1), "r"(a2), "r"(a3), "r"(b0), "r"(b1), "f"(0.f));
}
__device__ __forceinline__ uint32_t ld_rlx_u32(const void* p) {
    uint32_t v;
    asm volatile("ld.relaxed.gpu.global.u32 %0, [%1];" : "=r"(v) : "l"(p) : "memory");
    return v;
}
__device__ __forceinline__ uint64_t ld_rlx_u64(const void* p) {
    uint64_t v;
    asm volatile("ld.relaxed.gpu.global.u64 %0, [%1];" : "=l"(v) : "l"(p) : "memory");
    return v;
}
__device__ __forceinline__ uint4 ld_rlx_v4(const void* p) {
    uint4 v;
    asm volatile("ld.relaxed.gpu.global.v4.u32 {%0,%1,%2,%3}, [%4];"
                 : "=r"(v.x), "=r"(v.y), "=r"(v.z), "=r"(v.w) : "l"(p) : "memory");
    return v;
}
__device__ __forceinline__ void st_rlx_u32(void* p, uint32_t v) {
    asm volatile("st.relaxed.gpu.global.u32 [%0], %1;" ::"l"(p), "r"(v) : "memory");
}
__device__ __forceinline__ void st_rlx_u64(void* p, uint64_t v) {
    asm volatile("st.relaxed.gpu.global.u64 [%0], %1;" ::"l"(p), "l"(v) : "memory");
}
__device__ __forceinline__ void st_rlx_v4(void* p, uint4 v) {
    asm volatile("st.relaxed.gpu.global.v4.u32 [%0], {%1,%2,%3,%4};" ::"l"(p), "r"(v.x), "r"(v.y), "r"(v.z), "r"(v.w)
                 : "memory");
}
__device__ __forceinline__ uint4 ldg_stream128(const void* p) {
    uint4 v;
    asm volatile("ld.global.nc.L1::no_allocate.v4.u32 {%0,%1,%2,%3}, [%4];"
                 : "=r"(v.x), "=r"(v.y), "=r"(v.z), "=r"(v.w) : "l"(p));
    return v;
}
__device__ __forceinline__ void bar_consumers() { asm volatile("bar.sync 1, 256;" ::: "memory"); }
__device__ __forceinline__ uint32_t tag_f32(float v, uint32_t tag) { return (__float_as_uint(v) & ~0xFFu) | tag; }
__device__ __forceinline__ bool tagged4(const uint4& v, uint32_t tag) {
    return ((((v.x ^ tag) | (v.y ^ tag)) | ((v.z ^ tag) | (v.w ^ tag))) & 0xFFu) == 0;
}
__device__ __forceinline__ float untag(uint32_t v) { return __uint_as_float(v & ~0xFFu); }
__device__ __forceinline__ float bf_lo(uint32_t w) { return __uint_as_float(w << 16); }
__device__ __forceinline__ float bf_hi(uint32_t w) { return __uint_as_float(w & 0xFFFF0000u); }
__device__ __forceinline__ uint32_t pack_bf16(float lo, float hi) {
    uint32_t r;
    asm("cvt.rn.bf16x2.f32 %0, %1, %2;" : "=r"(r) : "f"(hi), "f"(lo));
    return r;
}
__device__ __forceinline__ float ex2(float x) {
    float y;
    asm("ex2.approx.ftz.f32 %0, %1;" : "=f"(y) : "f"(x));
    return y;
}

__global__ void __launch_bounds__(kThreads, 1)
decode_attn_kernel(const __nv_bfloat16* __restrict__ x, const __nv_bfloat16* __restrict__ kc,
                   const __nv_bfloat16* __restrict__ vc, const __nv_bfloat16* __restrict__ wq,
                   const __grid_constant__ CUtensorMap wo_map, __nv_bfloat16* __restrict__ out) {
    extern __shared__ __align__(128) unsigned char smem[];
    const int tid = threadIdx.x, lane = tid & 31;
    const int warp = __shfl_sync(0xffffffffu, tid >> 5, 0);
    const int cta = blockIdx.x;
    const int pair = cta >> 2, split = cta & 3;
    const int b = pair >> 4, j = pair & 15;
    const int rank = b * 4 + split;
    const int g = lane >> 2, t = lane & 3;
    const uint32_t sbase = smem_u32(smem);
    const uint32_t bar_full = sbase + kOffBar, bar_empty = bar_full + kItems * 8;
    const uint32_t bar_q = bar_empty + 2 * kTiles * 8, bar_stat = bar_q + 8;
    Scratch* sc = &g_scratch;
    if (warp == kConsumerWarps) {
        if (lane == 0) {
            TS(0);
            const char* kbase = (const char*)kc + ((size_t)pair * kSK + (kSK - kW) + split * 64) * (kDH * 2);
            uint64_t pol;
            asm volatile("createpolicy.fractional.L2::evict_first.b64 %0, 1.0;" : "=l"(pol));
#pragma unroll
            for (int n = 0; n < kStart; n++) mbar_init(bar_full + n * 8, 1);
            asm volatile("fence.mbarrier_init.release.cluster;" ::: "memory");
#pragma unroll
            for (int n = 0; n < kStart; n++) {
                mbar_expect_tx(bar_full + n * 8, kTileBytes);
                bulk_g2s(sbase + kOffRing + n * kTileBytes, kbase + (size_t)n * (4 * kTileBytes), kTileBytes,
                         bar_full + n * 8, pol);
            }
#pragma unroll 1
            for (int n = kStart; n < kNumBars; n++) mbar_init(bar_full + n * 8, 1);
            asm volatile("fence.mbarrier_init.release.cluster;" ::: "memory");
            asm volatile("prefetch.tensormap [%0];" ::"l"(&wo_map) : "memory");
            *(volatile uint32_t*)(smem + kOffMon) = 0xFFFFFFFFu;
            *(volatile uint32_t*)(smem + kOffMon + 4) = 0u;
        }
        __syncwarp();
        {
            const uint4 z = make_uint4(0, 0, 0, 0);
            st_rlx_v4(&sc->q[j][lane >> 4][rank >> 2][(rank & 3) * 64 + (lane & 15) * 4], z);
            float* cz = &sc->c[j][rank][0];
            st_rlx_v4(cz + lane * 4, z);
            st_rlx_v4(cz + 128 + lane * 4, z);
            if (lane < 2) st_rlx_v4(&sc->ml[pair][split][lane * 2], z);
            float* rz = &sc->r[rank][j][0];
            st_rlx_v4(rz + lane * 4, z);
            if (lane < 4) st_rlx_v4(rz + 128 + lane * 4, z);
        }
        asm volatile("bar.arrive 2, 320;" ::: "memory");
        if (lane == 0) {
            const char* kbase = (const char*)kc + ((size_t)pair * kSK + (kSK - kW) + split * 64) * (kDH * 2);
            const char* vbase = (const char*)vc + ((size_t)pair * kSK + (kSK - kW) + split * 64) * (kDH * 2) -
                                (size_t)kTiles * (4 * kTileBytes);
            uint64_t pol;
            asm volatile("createpolicy.fractional.L2::evict_first.b64 %0, 1.0;" : "=l"(pol));
            int next = kStart;
            bool q_ready = false;
            int reported = 0;
#pragma unroll 1
            for (int m = 0; next < kItems; m++) {
                mbar_wait(bar_full + m * 8, 0, 1000 + m);
                if ((m & 3) == 0) TS(16 + m);
                if (!q_ready) q_ready = mbar_test(bar_q, 0) || m >= kNSlot - kWin0 - 1;
                int win = q_ready ? (m >= K_END_AT ? K_END_WIN : kInflight) : kWin0;
                if (m < 2 * kTiles && m >= reported) {
                    asm volatile("red.relaxed.gpu.global.add.u32 [%0], 1;" ::"l"(&sc->landed) : "memory");
                    reported = m + 1;
                }
                if (q_ready) {
                    const uint32_t gl = *(volatile uint32_t*)(smem + kOffMon);
                    const int lag = (int)gl + K_BAL_BIAS - (m + 1) * 128;
                    if (gl != 0xFFFFFFFFu && m < K_BAL_UNTIL)
                        win += (lag > K_BAL_HI3) ? 3 : (lag > K_BAL_HI2) ? 2 : (lag > K_BAL_HI1) ? 1 : (lag < -K_BAL_LO2) ? -2 : (lag < -K_BAL_LO) ? -1 : 0;
                }
#pragma unroll 1
                while (next < kItems && next <= m + win) {
                    const int n = next++;
                    const uint32_t bar = bar_full + n * 8;
                    if (n < 2 * kTiles) {
                        if (n >= kNSlot) mbar_wait(bar_empty + (n - kNSlot) * 8, 0, 2000 + n);
                        mbar_expect_tx(bar, kTileBytes);
                        bulk_g2s(sbase + kOffRing + (n % kNSlot) * kTileBytes,
                                 (n < kTiles ? kbase : vbase) + (size_t)n * (4 * kTileBytes), kTileBytes, bar, pol);
                    } else {
                        if (n == 2 * kTiles) {
#pragma unroll 1
                            for (int u = 0; u < 3; u++) mbar_wait(bar_empty + (kNSlot + kWoSlot + u) * 8, 0, 2600);
                        }
                        const int part = n - 2 * kTiles;
                        mbar_expect_tx(bar, kWoBytes / kNWo);
                        tma_2d(sbase + kOffRing + kWoSlot * kTileBytes + part * (kWoBytes / kNWo), &wo_map, rank * kWoCols,
                               j * 256 + part * kWoRows, bar, pol);
                        if (n == kItems - 1) TS(1);
                    }
                }
            }
            *(volatile uint32_t*)(smem + kOffMon + 4) = 1u;
            asm volatile("red.relaxed.gpu.global.add.u32 [%0], %1;" ::"l"(&sc->landed), "r"(2 * kTiles - reported) : "memory");
        }
        return;
    }
    if (warp == kConsumerWarps + 2) {
        asm volatile("bar.sync 2, 320;" ::: "memory");
        if (lane == 0) {
            const uint32_t base = *(volatile uint32_t*)(smem + kOffX + 1156) * 4096u;
            uint32_t it = 0;
            while (*(volatile uint32_t*)(smem + kOffMon + 4) == 0u && ++it < kSpinLimit)
                *(volatile uint32_t*)(smem + kOffMon) = ld_rlx_u32(&sc->landed) - base;
        }
        return;
    }
    if (warp == kConsumerWarps + 1) {
        asm volatile("bar.sync 3, 288;" ::: "memory");
        const uint32_t tag = *(const uint32_t*)(smem + kOffX + 1152);
        const int hd = lane >> 4;
        const float2 v = *((const float2*)(smem + kOffML) + (lane & 15) * 2 + hd);
        float M = v.x;
#pragma unroll
        for (int o = 1; o < 16; o <<= 1) M = fmaxf(M, __shfl_xor_sync(0xffffffffu, M, o));
        float L = v.y * ex2(v.x - M);
#pragma unroll
        for (int o = 1; o < 16; o <<= 1) L += __shfl_xor_sync(0xffffffffu, L, o);
        if ((lane & 15) == 0) st_rlx_u64(&sc->ml[pair][split][hd], ((uint64_t)tag_f32(L, tag) << 32) | __float_as_uint(M));
        const unsigned long long* src = &sc->ml[pair][lane & 3][hd];
        uint64_t w;
        uint32_t it = 0;
        while (true) {
            w = ld_rlx_u64(src);
            if (__all_sync(0xffffffffu, (((uint32_t)(w >> 32)) & 0xFFu) == tag)) break;
            __nanosleep(200);
            if (++it > kSpinLimit) SPIN_FAIL(105);
        }
        const float Mi = __uint_as_float((uint32_t)w), Li = untag((uint32_t)(w >> 32));
        float Mg = fmaxf(Mi, __shfl_xor_sync(0xffffffffu, Mi, 1));
        Mg = fmaxf(Mg, __shfl_xor_sync(0xffffffffu, Mg, 2));
        float Lg = Li * ex2(Mi - Mg);
        Lg += __shfl_xor_sync(0xffffffffu, Lg, 1);
        Lg += __shfl_xor_sync(0xffffffffu, Lg, 2);
        if ((lane & 15) == 0) *((float2*)(smem + kOffML + 256) + hd) = make_float2(Mg, 1.f / Lg);
        __syncwarp();
        if (lane == 0) mbar_arrive(bar_stat);
        return;
    }
    uint32_t tag;
    {
        uint4 wv[9];
        uint32_t xb[9];
        {
            const int row0 = (rank >> 2) * 288 + warp * 36 + t;
            const char* wp = (const char*)wq + ((size_t)row0 * 4096 + j * 256 + (rank & 3) * 64 + g * 8) * 2;
#pragma unroll
            for (int i = 0; i < 9; i++) wv[i] = ldg_stream128(wp + (size_t)i * (4 * 4096 * 2));
        }
        if (tid < 72) {
            const int bb = tid >= 36 ? 1 : 0;
            const uint4 xv = __ldg((const uint4*)(x + bb * kD + (rank >> 2) * 288) + (tid - bb * 36));
            *(uint4*)(smem + kOffX + tid * 16) = xv;
        } else if (tid == 96) {
            const uint32_t ep = ld_rlx_u32(&sc->epoch);
            *(uint2*)(smem + kOffX + 1152) = make_uint2(ep % 255u + 1u, ep);
        }
        bar_consumers();
        {
            const unsigned short* xs = (const unsigned short*)(smem + kOffX) + ((g >> 1) & 1) * 288 + warp * 36 + t;
#pragma unroll
            for (int i = 0; i < 9; i++) xb[i] = xs[4 * i];
            tag = *(const uint32_t*)(smem + kOffX + 1152);
        }
        float* my_q = &sc->q[j][(tid >> 6) & 1][rank >> 2][(rank & 3) * 64 + (tid & 63)];
        float* my_c = &sc->c[j][rank][tid];
        {
            float qa[4], qb[4];
            const int sh = (g & 1) * 16;
#pragma unroll
            for (int i = 0; i < 9; i++) xb[i] <<= sh;
            mma_bf16_z(qa, wv[0].x, wv[0].z, wv[1].x, wv[1].z, xb[0], xb[1]);
            mma_bf16_z(qb, wv[0].y, wv[0].w, wv[1].y, wv[1].w, xb[0], xb[1]);
#pragma unroll
            for (int u = 1; u < 4; u++) {
                mma_bf16(qa, wv[2 * u].x, wv[2 * u].z, wv[2 * u + 1].x, wv[2 * u + 1].z, xb[2 * u], xb[2 * u + 1]);
                mma_bf16(qb, wv[2 * u].y, wv[2 * u].w, wv[2 * u + 1].y, wv[2 * u + 1].w, xb[2 * u], xb[2 * u + 1]);
            }
            mma_bf16(qa, wv[8].x, wv[8].z, 0u, 0u, xb[8], 0u);
            mma_bf16(qb, wv[8].y, wv[8].w, 0u, 0u, xb[8], 0u);
            if (tid == 0) TS(2);
            float* part = (float*)(smem + kOffRed);
            if (t < 2) {
                float4* dst = (float4*)(part + (warp * 2 + t) * 64 + g * 8);
                dst[0] = make_float4(qa[0], qa[1], qb[0], qb[1]);
                dst[1] = make_float4(qa[2], qa[3], qb[2], qb[3]);
            }
            asm volatile("bar.sync 2, 320;" ::: "memory");
            if (tid < 128) {
                float s0 = 0.f;
#pragma unroll
                for (int w = 0; w < 8; w++) s0 += part[w * 128 + tid];
                st_rlx_u32(my_q, tag_f32(s0, tag));
            }
            const float* src = &sc->q[j][b][0][tid];
            uint32_t v0 = ld_rlx_u32(src), v1 = ld_rlx_u32(src + 256);
            uint32_t it = 0;
            while ((v0 & 0xFFu) != tag || (v1 & 0xFFu) != tag) {
                __nanosleep(100);
                if ((v0 & 0xFFu) != tag) v0 = ld_rlx_u32(src);
                if ((v1 & 0xFFu) != tag) v1 = ld_rlx_u32(src + 256);
                if (++it > kSpinLimit) SPIN_FAIL(101);
            }
            ((__nv_bfloat16*)(smem + kOffQ))[tid] = __float2bfloat16(untag(v0) + untag(v1));
            bar_consumers();
            if (tid == 0) mbar_arrive(bar_q);
        }
        if (tid == 0) TS(3);
        uint4 qf[4];
#pragma unroll
        for (int i = 0; i < 4; i++)
            qf[i] = lds128(sbase + kOffQ + (g & 1) * 256 + (4 * (i ^ ((g >> 1) & 1)) + t) * 16);

        float m0 = 0.f, m1 = 0.f;
#pragma unroll 1
        for (int h = 0; h < 2; h++) {
            const int n = warp + 8 * h;
            mbar_wait(bar_full + n * 8, 0);
            const uint32_t kb = sbase + kOffRing + (n % kNSlot) * kTileBytes + g * 512 + t * 16;
            float s[4][4];
#pragma unroll
            for (int mt = 0; mt < 4; mt++) {
#pragma unroll
                for (int i = 0; i < 4; i++) {
                    const uint32_t addr = kb + mt * 4096 + ((i ^ (g & 1)) * 64);
                    const uint4 ra = lds128(addr), rb = lds128(addr + 256);
                    if (i == 0) mma_bf16_z(s[mt], ra.x, rb.x, ra.y, rb.y, qf[i].x, qf[i].y);
                    else mma_bf16(s[mt], ra.x, rb.x, ra.y, rb.y, qf[i].x, qf[i].y);
                    mma_bf16(s[mt], ra.z, rb.z, ra.w, rb.w, qf[i].z, qf[i].w);
                }
            }
            __syncwarp();
            if (lane == 0) mbar_arrive(bar_empty + n * 8);
            const bool valid = ((t ^ g) & 1) == 0;
            const bool hi = t >= 2;
            float e0[4], e1[4];
            float m = -INFINITY;
#pragma unroll
            for (int i = 0; i < 4; i++) {
                e0[i] = valid ? (hi ? s[i][1] : s[i][0]) : -INFINITY;
                e1[i] = valid ? (hi ? s[i][3] : s[i][2]) : -INFINITY;
                m = fmaxf(m, fmaxf(e0[i], e1[i]));
            }
            m = fmaxf(m, __shfl_xor_sync(0xffffffffu, m, 1));
            m = fmaxf(m, __shfl_xor_sync(0xffffffffu, m, 4));
            m = fmaxf(m, __shfl_xor_sync(0xffffffffu, m, 8));
            m = fmaxf(m, __shfl_xor_sync(0xffffffffu, m, 16));
            const float mw = m * kScaleLog2;
            float l = 0.f;
            uint32_t* ps = (uint32_t*)(smem + kOffP + warp * 512 + h * 256) + (t >> 1) * 32 + (g & 3) * 8 + (g >> 2);
#pragma unroll
            for (int i = 0; i < 4; i++) {
                const float p0 = ex2(fmaf(e0[i], kScaleLog2, -mw)), p1 = ex2(fmaf(e1[i], kScaleLog2, -mw));
                l += p0 + p1;
                if (valid) ps[2 * i] = pack_bf16(p0, p1);
            }
            l += __shfl_xor_sync(0xffffffffu, l, 1);
            l += __shfl_xor_sync(0xffffffffu, l, 4);
            l += __shfl_xor_sync(0xffffffffu, l, 8);
            l += __shfl_xor_sync(0xffffffffu, l, 16);
            if (lane == 0 || lane == 2) *((float2*)(smem + kOffML) + n * 2 + (t >> 1)) = make_float2(mw, l);
            if (h == 0) m0 = mw; else m1 = mw;
        }
        __syncwarp();
        asm volatile("bar.arrive 3, 288;" ::: "memory");
        if (tid == 0) TS(4);
        m0 = __shfl_sync(0xffffffffu, m0, (lane & 28) + 2 * (t & 1));
        m1 = __shfl_sync(0xffffffffu, m1, (lane & 28) + 2 * (t & 1));

        float o[4][4];
        const bool bval = (t & 1) == (g >> 2);
        const uint32_t sel0 = bval ? ((g & 1) ? 0x1044u : 0x4410u) : 0x4444u;
        const uint32_t sel1 = bval ? ((g & 1) ? 0x3244u : 0x4432u) : 0x4444u;
#pragma unroll 1
        for (int h = 0; h < 2; h++) {
            const uint32_t pa = sbase + kOffP + warp * 512 + h * 256 + ((g >> 1) & 1) * 128 + t * 32;
            const uint4 pA = lds128(pa), pB = lds128(pa + 16);
            const uint32_t pw[8] = {pA.x, pA.y, pA.z, pA.w, pB.x, pB.y, pB.z, pB.w};
            const int n = kTiles + warp + 8 * h;
            float f1 = 0.f;
            if (h == 1) {
                mbar_wait(bar_stat, 0);
                const float2 st = *((const float2*)(smem + kOffML + 256) + (t & 1));
                const float f0 = ex2(m0 - st.x) * st.y;
                f1 = ex2(m1 - st.x) * st.y;
#pragma unroll
                for (int i = 0; i < 4; i++)
#pragma unroll
                    for (int c = 0; c < 4; c++) o[i][c] *= f0;
            }
            mbar_wait(bar_full + n * 8, 0);
            const uint32_t vb = sbase + kOffRing + (n % kNSlot) * kTileBytes + t * 512 + ((g ^ ((t & 1) * 4)) * 16);
            float acc[4][4];
#pragma unroll
            for (int r = 0; r < 8; r++) {
                const uint32_t addr = vb + r * 2048;
                const uint4 l0v = lds128(addr), l1v = lds128(addr + 128), l2v = lds128(addr + 256), l3v = lds128(addr + 384);
                const uint32_t b0 = __byte_perm(pw[r], 0, sel0), b1 = __byte_perm(pw[r], 0, sel1);
                if (r == 0) {
                    mma_bf16_z(acc[0], l0v.x, l1v.x, l2v.x, l3v.x, b0, b1);
                    mma_bf16_z(acc[1], l0v.y, l1v.y, l2v.y, l3v.y, b0, b1);
                    mma_bf16_z(acc[2], l0v.z, l1v.z, l2v.z, l3v.z, b0, b1);
                    mma_bf16_z(acc[3], l0v.w, l1v.w, l2v.w, l3v.w, b0, b1);
                } else {
                    mma_bf16(acc[0], l0v.x, l1v.x, l2v.x, l3v.x, b0, b1);
                    mma_bf16(acc[1], l0v.y, l1v.y, l2v.y, l3v.y, b0, b1);
                    mma_bf16(acc[2], l0v.z, l1v.z, l2v.z, l3v.z, b0, b1);
                    mma_bf16(acc[3], l0v.w, l1v.w, l2v.w, l3v.w, b0, b1);
                }
            }
            __syncwarp();
            if (lane == 0) mbar_arrive(bar_empty + n * 8);
#pragma unroll
            for (int i = 0; i < 4; i++)
#pragma unroll
                for (int c = 0; c < 4; c++) o[i][c] = h == 0 ? acc[i][c] : fmaf(f1, acc[i][c], o[i][c]);
        }
        if (tid == 0) TS(5);
        {
            float* red = (float*)(smem + kOffRed);
            float4* dst = (float4*)(red + (warp * 4 + t) * 128   + (g ^ ((t >> 1) * 4)) * 8);
            dst[0] = make_float4(o[0][0], o[0][1], o[1][0], o[1][1]);
            dst[1] = make_float4(o[2][0], o[2][1], o[3][0], o[3][1]);
            dst[16] = make_float4(o[0][2], o[0][3], o[1][2], o[1][3]);
            dst[17] = make_float4(o[2][2], o[2][3], o[3][2], o[3][3]);
            bar_consumers();
            const float* rp = red + tid;
            float a0 = 0.f, a1 = 0.f;
#pragma unroll
            for (int w = 0; w < 8; w++) {
                a0 += rp[w * 512];
                a1 += rp[w * 512 + 256];
            }
            st_rlx_u32(my_c, tag_f32(a0 + a1, tag));
        }
        if (tid == 0) TS(6);
    }

    {
        const int pq = lane >> 3;
        const float* src = &sc->c[j][pq][warp * 32 + (lane & 7) * 4];
        uint4 v0 = ld_rlx_v4(src), v1 = ld_rlx_v4(src + 4 * 256), u0, u1;
        uint4 wa[5][2];
        bool have_wo = false;
        const uint32_t bar_wo = bar_full + (2 * kTiles + (warp * 32) / kWoRows) * 8;
        const uint32_t wbase = sbase + kOffRing + kWoSlot * kTileBytes +
                               (warp * 32 + (lane & 7) + ((lane >> 4) & 1) * 8) * (kWoCols * 2) + ((lane >> 3) & 1) * 16;
        { const long long c0 = clock64(); while (clock64() - c0 < 170) {} }
        u0 = ld_rlx_v4(src); u1 = ld_rlx_v4(src + 4 * 256);
        {
            uint32_t it = 0;
            while (true) {
                if (!have_wo && __all_sync(0xffffffffu, mbar_test(bar_wo, 0))) {
#pragma unroll
                    for (int mt = 0; mt < 5; mt++) {
                        wa[mt][0] = ldsm_x4_trans(wbase + mt * 32);
                        wa[mt][1] = ldsm_x4_trans(wbase + 16 * (kWoCols * 2) + mt * 32);
                    }
                    have_wo = true;
                }
                const bool ok0 = tagged4(v0, tag), ok1 = tagged4(v1, tag);
                if (__all_sync(0xffffffffu, ok0 && ok1)) break;
                if (!ok0) v0 = ld_rlx_v4(src);
                if (!ok1) v1 = ld_rlx_v4(src + 4 * 256);
                const bool pk0 = tagged4(u0, tag), pk1 = tagged4(u1, tag);
                if (__all_sync(0xffffffffu, pk0 && pk1)) { v0 = u0; v1 = u1; break; }
                if (!pk0) u0 = ld_rlx_v4(src);
                if (!pk1) u1 = ld_rlx_v4(src + 4 * 256);
                if (++it > kSpinLimit) SPIN_FAIL(102);
            }
        }
        {
            const bool hb = pq >= 2, hr = (pq & 1) != 0;
            const float a[4] = {untag(v0.x), untag(v0.y), untag(v0.z), untag(v0.w)};
            const float c[4] = {untag(v1.x), untag(v1.y), untag(v1.z), untag(v1.w)};
            float k[4];
#pragma unroll
            for (int e = 0; e < 4; e++)
                k[e] = (hb ? c[e] : a[e]) + __shfl_xor_sync(0xffffffffu, hb ? a[e] : c[e], 16);
            const float r0 = (hr ? k[2] : k[0]) + __shfl_xor_sync(0xffffffffu, hr ? k[0] : k[2], 8);
            const float r1 = (hr ? k[3] : k[1]) + __shfl_xor_sync(0xffffffffu, hr ? k[1] : k[3], 8);
            *(uint32_t*)(smem + kOffO + (pq >> 1) * 512 + (warp * 32 + (lane & 7) * 4 + (pq & 1) * 2) * 2) = pack_bf16(r0, r1);
            __syncwarp();
        }
        if (tid == 0) TS(7);
        if (lane == 0) TS(104 + warp);
        float acc[5][4];
        {
            uint32_t bq[2][2];
#pragma unroll
            for (int ks = 0; ks < 2; ks++) {
                const uint32_t* ow = (const uint32_t*)(smem + kOffO + (g & 1) * 512) + warp * 16 + ks * 8 + t;
                bq[ks][0] = g < 2 ? ow[0] : 0u;
                bq[ks][1] = g < 2 ? ow[4] : 0u;
            }
            if (!have_wo) {
                mbar_wait(bar_wo, 0, 3000);
#pragma unroll
                for (int mt = 0; mt < 5; mt++) {
                    wa[mt][0] = ldsm_x4_trans(wbase + mt * 32);
                    wa[mt][1] = ldsm_x4_trans(wbase + 16 * (kWoCols * 2) + mt * 32);
                }
            }
            if (tid == 0) TS(8);
#pragma unroll
            for (int mt = 0; mt < 5; mt++) {
                mma_bf16_z(acc[mt], wa[mt][0].x, wa[mt][0].y, wa[mt][0].z, wa[mt][0].w, bq[0][0], bq[0][1]);
                mma_bf16(acc[mt], wa[mt][1].x, wa[mt][1].y, wa[mt][1].z, wa[mt][1].w, bq[1][0], bq[1][1]);
            }
        }
        {
            float* part = (float*)(smem + kOffPart);
            if (t == 0) {
#pragma unroll
                for (int mt = 0; mt < 5; mt++) {
                    part[(warp * 2 + 0) * 80 + mt * 16 + g] = acc[mt][0];
                    part[(warp * 2 + 1) * 80 + mt * 16 + g] = acc[mt][1];
                    part[(warp * 2 + 0) * 80 + mt * 16 + g + 8] = acc[mt][2];
                    part[(warp * 2 + 1) * 80 + mt * 16 + g + 8] = acc[mt][3];
                }
            }
            if (lane == 0) TS(96 + warp);
            bar_consumers();
            if (tid < 144) {
                const int bb = tid >= 72 ? 1 : 0, col = tid - bb * 72;
                float sum = 0.f;
#pragma unroll
                for (int w = 0; w < 8; w++) sum += part[(w * 2 + bb) * 80 + col];
                if (lane == 0) TS(64 + warp);
                st_rlx_u32(&sc->r[rank][j][tid], tag_f32(sum, tag));
            }
        }
        if (tid == 0) TS(9);
        if (warp >= 5 && j < 9) {
            const int pq8 = lane >> 2;
            const float* rsrc = &sc->r[rank][pq8][j * 16 + (lane & 3) * 4];
            if (warp > 5) { const long long c0 = clock64(); while (clock64() - c0 < (warp - 5) * 110) {} }
            if (lane == 0) TS(72 + warp);
            uint4 w0 = ld_rlx_v4(rsrc), w1 = ld_rlx_v4(rsrc + 8 * 144);
            uint32_t it = 0;
            while (true) {
                const bool ok0 = tagged4(w0, tag), ok1 = tagged4(w1, tag);
                if (__all_sync(0xffffffffu, ok0 && ok1)) break;
                if (!ok0) w0 = ld_rlx_v4(rsrc);
                if (!ok1) w1 = ld_rlx_v4(rsrc + 8 * 144);
                if (++it > kSpinLimit) SPIN_FAIL(103);
            }
            if (lane == 0) TS(80 + warp);
            const float x0 = untag(w0.x) + untag(w1.x), x1 = untag(w0.y) + untag(w1.y);
            const float x2 = untag(w0.z) + untag(w1.z), x3 = untag(w0.w) + untag(w1.w);
            const bool h2 = pq8 >= 4, h1 = (pq8 & 2) != 0;
            const float y0 = (h2 ? x2 : x0) + __shfl_xor_sync(0xffffffffu, h2 ? x0 : x2, 16);
            const float y1 = (h2 ? x3 : x1) + __shfl_xor_sync(0xffffffffu, h2 ? x1 : x3, 16);
            float z = (h1 ? y1 : y0) + __shfl_xor_sync(0xffffffffu, h1 ? y0 : y1, 8);
            z += __shfl_xor_sync(0xffffffffu, z, 4);
            if ((pq8 & 1) == 0) {
                const int e = j * 16 + (lane & 3) * 4 + (h2 ? 2 : 0) + (h1 ? 1 : 0);
                const int bb = e >= 72 ? 1 : 0;
                out[bb * kD + rank * kWoCols + (e - bb * 72)] = __float2bfloat16(z);
            }
            if (cta == 0 && warp == 5 && lane == 0) st_rlx_u32(&sc->epoch, ld_rlx_u32(&sc->epoch) + 1u);
            if (warp == 5 && lane == 0) TS(10);
        }
    }
}

}

typedef CUresult (*EncodeTiledFn)(CUtensorMap*, CUtensorMapDataType, cuuint32_t, void*, const cuuint64_t*,
                                  const cuuint64_t*, const cuuint32_t*, const cuuint32_t*, CUtensorMapInterleave,
                                  CUtensorMapSwizzle, CUtensorMapL2promotion, CUtensorMapFloatOOBfill);

extern "C" void kernel_launch(void* const* d_in, const int* in_sizes, int n_in, void* d_out, int out_size) {
    (void)in_sizes; (void)n_in; (void)out_size;
    static EncodeTiledFn encode = nullptr;
    if (!encode) {
        void* fn = nullptr;
        cudaDriverEntryPointQueryResult st;
        cudaGetDriverEntryPoint("cuTensorMapEncodeTiled", &fn, cudaEnableDefault, &st);
        encode = (EncodeTiledFn)fn;
        cudaFuncSetAttribute(decode_attn_kernel, cudaFuncAttributeMaxDynamicSharedMemorySize, kSmemBytes + 1024);
    }
    CUtensorMap wo_map;
    const cuuint64_t dims[2] = {(cuuint64_t)kD, 4096};
    const cuuint64_t strides[1] = {(cuuint64_t)kD * 2};
    const cuuint32_t box[2] = {(cuuint32_t)kWoCols, (cuuint32_t)kWoRows};
    const cuuint32_t estr[2] = {1, 1};
    encode(&wo_map, CU_TENSOR_MAP_DATA_TYPE_BFLOAT16, 2, d_in[4], dims, strides, box, estr,
           CU_TENSOR_MAP_INTERLEAVE_NONE, CU_TENSOR_MAP_SWIZZLE_NONE, CU_TENSOR_MAP_L2_PROMOTION_L2_256B,
           CU_TENSOR_MAP_FLOAT_OOB_FILL_NONE);
    decode_attn_kernel<<<kNCTA, kThreads, kSmemBytes + kTsBytes, cudaStreamPerThread>>>(
        (const __nv_bfloat16*)d_in[0], (const __nv_bfloat16*)d_in[1], (const __nv_bfloat16*)d_in[2],
        (const __nv_bfloat16*)d_in[3], wo_map, (__nv_bfloat16*)d_out);
}
```

```cpp
#define X_LATE
#include <cuda_runtime.h>
#include <cuda.h>
#include <cuda_bf16.h>
#include <stdint.h>

namespace {

constexpr int kD = 576, kSK = 32768, kDH = 128, kW = 4096;
constexpr int kNCTA = 128;
constexpr int kConsumerWarps = 8;
#define K_BAL 1
#define K_BAL_BIAS 200
#define K_BAL_HI1 64
#define K_BAL_HI2 192
#define K_BAL_LO 96
#define K_INFLIGHT 4
#define K_START 3
#define K_WIN0 3
#define K_DELAY 0
#define K_END_AT 28
#define K_END_WIN 2
constexpr int kThreads = 320;
constexpr int kTileBytes = 16384;
constexpr int kNSlot = 6;
constexpr int kInflight = K_INFLIGHT;
constexpr int kStart = K_START;
constexpr int kWin0 = K_WIN0;
constexpr int kTiles = 16;
constexpr int kNWo = 2;
constexpr int kWoRows = 256 / kNWo;
constexpr int kWoCols = 72;
constexpr int kWoBytes = 256 * kWoCols * 2;
constexpr int kWoSlot = 2;
constexpr int kItems = 2 * kTiles + kNWo;

constexpr int kOffRing = 0;
constexpr int kOffA = kOffRing + kNSlot * kTileBytes;
constexpr int kOffC = kOffA + 8192;
constexpr int kOffQin = kOffC;
constexpr int kOffX = kOffC + 2048;
constexpr int kOffQ = kOffC + 3328;
constexpr int kOffML = kOffC + 8192;
constexpr int kOffMon = kOffML + 256 + 16 + 128;
constexpr int kNumBars = kItems + 2 * kTiles + 6;
constexpr int kOffBar = kOffMon + 8;
constexpr int kSmemBytes = kOffBar + kNumBars * 8;
static_assert(kSmemBytes <= 115712, "two CTAs per SM");

constexpr float kScaleLog2 = 0.08838834764831845f * 1.4426950408889634f;
constexpr uint32_t kSpinLimit = 1u << 22;

struct Scratch {
    float r[8][16][144];
    unsigned epoch;
    unsigned pad[31];
    unsigned landed;
};
__device__ Scratch g_scratch;

#define TS(i) do { } while (0)

#define SPIN_FAIL(id) __trap()

__device__ __forceinline__ uint32_t smem_u32(const void* p) { return (uint32_t)__cvta_generic_to_shared(p); }
__device__ __forceinline__ void mbar_init(uint32_t bar, uint32_t cnt) {
    asm volatile("mbarrier.init.shared::cta.b64 [%0], %1;" ::"r"(bar), "r"(cnt) : "memory");
}
__device__ __forceinline__ void mbar_expect_tx(uint32_t bar, uint32_t bytes) {
    asm volatile("mbarrier.arrive.expect_tx.shared::cta.b64 _, [%0], %1;" ::"r"(bar), "r"(bytes) : "memory");
}
__device__ __forceinline__ void mbar_arrive(uint32_t bar) {
    asm volatile("mbarrier.arrive.shared::cta.b64 _, [%0];" ::"r"(bar) : "memory");
}
__device__ __forceinline__ void mbar_wait(uint32_t bar, uint32_t parity, int id = 0) {
    uint32_t done, it = 0;
    do {
        asm volatile(
            "{\n.reg .pred p;\n"
            "mbarrier.try_wait.parity.shared::cta.b64 p, [%1], %2;\n"
            "selp.u32 %0, 1, 0, p;\n}"
            : "=r"(done) : "r"(bar), "r"(parity) : "memory");
        if (++it > kSpinLimit) SPIN_FAIL(id);
    } while (!done);
}
__device__ __forceinline__ void mbar_wait_cluster(uint32_t bar, uint32_t parity, int id = 0) {
    uint32_t done, it = 0;
    do {
        asm volatile(
            "{\n.reg .pred p;\n"
            "mbarrier.try_wait.parity.acquire.cluster.shared::cta.b64 p, [%1], %2;\n"
            "selp.u32 %0, 1, 0, p;\n}"
            : "=r"(done) : "r"(bar), "r"(parity) : "memory");
        if (++it > kSpinLimit) SPIN_FAIL(id);
    } while (!done);
}
__device__ __forceinline__ bool mbar_test(uint32_t bar, uint32_t parity) {
    uint32_t done;
    asm volatile(
        "{\n.reg .pred p;\n"
        "mbarrier.test_wait.parity.shared::cta.b64 p, [%1], %2;\n"
        "selp.u32 %0, 1, 0, p;\n}"
        : "=r"(done) : "r"(bar), "r"(parity) : "memory");
    return done != 0;
}
__device__ __forceinline__ bool mbar_test_cluster(uint32_t bar, uint32_t parity) {
    uint32_t done;
    asm volatile(
        "{\n.reg .pred p;\n"
        "mbarrier.test_wait.parity.acquire.cluster.shared::cta.b64 p, [%1], %2;\n"
        "selp.u32 %0, 1, 0, p;\n}"
        : "=r"(done) : "r"(bar), "r"(parity) : "memory");
    return done != 0;
}
__device__ __forceinline__ uint32_t mapa(uint32_t addr, uint32_t rank) {
    uint32_t r;
    asm("mapa.shared::cluster.u32 %0, %1, %2;" : "=r"(r) : "r"(addr), "r"(rank));
    return r;
}
__device__ __forceinline__ void st_async_u32(uint32_t raddr, uint32_t v, uint32_t rbar) {
    asm volatile("st.async.weak.shared::cluster.mbarrier::complete_tx::bytes.u32 [%0], %1, [%2];"
                 ::"r"(raddr), "r"(v), "r"(rbar) : "memory");
}
__device__ __forceinline__ void st_async_u64(uint32_t raddr, uint64_t v, uint32_t rbar) {
    asm volatile("st.async.weak.shared::cluster.mbarrier::complete_tx::bytes.u64 [%0], %1, [%2];"
                 ::"r"(raddr), "l"(v), "r"(rbar) : "memory");
}
__device__ __forceinline__ void cluster_arrive() { asm volatile("barrier.cluster.arrive.relaxed.aligned;" ::: "memory"); }
__device__ __forceinline__ void cluster_wait() { asm volatile("barrier.cluster.wait.acquire.aligned;" ::: "memory"); }
__device__ __forceinline__ void bulk_g2s(uint32_t dst, const void* src, uint32_t bytes, uint32_t bar, uint64_t pol) {
    asm volatile(
        "cp.async.bulk.shared::cluster.global.mbarrier::complete_tx::bytes.L2::cache_hint [%0], [%1], %2, [%3], %4;"
        ::"r"(dst), "l"(src), "r"(bytes), "r"(bar), "l"(pol) : "memory");
}
__device__ __forceinline__ void tma_2d(uint32_t dst, const CUtensorMap* map, int c0, int c1, uint32_t bar, uint64_t pol) {
    asm volatile(
        "cp.async.bulk.tensor.2d.shared::cluster.global.mbarrier::complete_tx::bytes.L2::cache_hint"
        " [%0], [%1, {%3, %4}], [%2], %5;"
        ::"r"(dst), "l"(map), "r"(bar), "r"(c0), "r"(c1), "l"(pol) : "memory");
}
__device__ __forceinline__ uint4 ldsm_x4_trans(uint32_t addr) {
    uint4 v;
    asm volatile("ldmatrix.sync.aligned.m8n8.x4.trans.shared.b16 {%0,%1,%2,%3}, [%4];"
                 : "=r"(v.x), "=r"(v.y), "=r"(v.z), "=r"(v.w) : "r"(addr) : "memory");
    return v;
}
__device__ __forceinline__ uint4 lds128(uint32_t addr) {
    uint4 v;
    asm volatile("ld.shared.v4.u32 {%0,%1,%2,%3}, [%4];" : "=r"(v.x), "=r"(v.y), "=r"(v.z), "=r"(v.w) : "r"(addr));
    return v;
}
__device__ __forceinline__ void mma_bf16(float (&c)[4], uint32_t a0, uint32_t a1, uint32_t a2, uint32_t a3,
                                         uint32_t b0, uint32_t b1) {
    asm volatile(
        "mma.sync.aligned.m16n8k16.row.col.f32.bf16.bf16.f32 {%0,%1,%2,%3}, {%4,%5,%6,%7}, {%8,%9}, {%0,%1,%2,%3};"
        : "+f"(c[0]), "+f"(c[1]), "+f"(c[2]), "+f"(c[3])
        : "r"(a0), "r"(a1), "r"(a2), "r"(a3), "r"(b0), "r"(b1));
}
__device__ __forceinline__ void mma_bf16_z(float (&c)[4], uint32_t a0, uint32_t a1, uint32_t a2, uint32_t a3,
                                           uint32_t b0, uint32_t b1) {
    asm volatile(
        "mma.sync.aligned.m16n8k16.row.col.f32.bf16.bf16.f32 {%0,%1,%2,%3}, {%4,%5,%6,%7}, {%8,%9}, {%10,%10,%10,%10};"
        : "=f"(c[0]), "=f"(c[1]), "=f"(c[2]), "=f"(c[3])
        : "r"(a0), "r"(a1), "r"(a2), "r"(a3), "r"(b0), "r"(b1), "f"(0.f));
}
__device__ __forceinline__ uint32_t ld_rlx_u32(const void* p) {
    uint32_t v;
    asm volatile("ld.relaxed.gpu.global.u32 %0, [%1];" : "=r"(v) : "l"(p) : "memory");
    return v;
}
__device__ __forceinline__ uint4 ld_rlx_v4(const void* p) {
    uint4 v;
    asm volatile("ld.relaxed.gpu.global.v4.u32 {%0,%1,%2,%3}, [%4];"
                 : "=r"(v.x), "=r"(v.y), "=r"(v.z), "=r"(v.w) : "l"(p) : "memory");
    return v;
}
__device__ __forceinline__ void st_rlx_u32(void* p, uint32_t v) {
    asm volatile("st.relaxed.gpu.global.u32 [%0], %1;" ::"l"(p), "r"(v) : "memory");
}
__device__ __forceinline__ void st_rlx_v4(void* p, uint4 v) {
    asm volatile("st.relaxed.gpu.global.v4.u32 [%0], {%1,%2,%3,%4};" ::"l"(p), "r"(v.x), "r"(v.y), "r"(v.z), "r"(v.w)
                 : "memory");
}
__device__ __forceinline__ uint4 ldg_stream128(const void* p) {
    uint4 v;
    asm volatile("ld.global.nc.L1::no_allocate.v4.u32 {%0,%1,%2,%3}, [%4];"
                 : "=r"(v.x), "=r"(v.y), "=r"(v.z), "=r"(v.w) : "l"(p));
    return v;
}
__device__ __forceinline__ void bar_consumers() { asm volatile("bar.sync 1, 256;" ::: "memory"); }
__device__ __forceinline__ uint32_t tag_f32(float v, uint32_t tag) { return (__float_as_uint(v) & ~0xFFu) | tag; }
__device__ __forceinline__ bool tagged4(const uint4& v, uint32_t tag) {
    return ((((v.x ^ tag) | (v.y ^ tag)) | ((v.z ^ tag) | (v.w ^ tag))) & 0xFFu) == 0;
}
__device__ __forceinline__ float untag(uint32_t v) { return __uint_as_float(v & ~0xFFu); }
__device__ __forceinline__ uint32_t pack_bf16(float lo, float hi) {
    uint32_t r;
    asm("cvt.rn.bf16x2.f32 %0, %1, %2;" : "=r"(r) : "f"(hi), "f"(lo));
    return r;
}
__device__ __forceinline__ float ex2(float x) {
    float y;
    asm("ex2.approx.ftz.f32 %0, %1;" : "=f"(y) : "f"(x));
    return y;
}

__global__ void __cluster_dims__(8, 1, 1) __launch_bounds__(kThreads, 2)
decode_attn_kernel(const __nv_bfloat16* __restrict__ x, const __nv_bfloat16* __restrict__ kc,
                   const __nv_bfloat16* __restrict__ vc, const __nv_bfloat16* __restrict__ wq,
                   const __grid_constant__ CUtensorMap wo_map, __nv_bfloat16* __restrict__ out) {
    extern __shared__ __align__(128) unsigned char smem[];
    const int tid = threadIdx.x, lane = tid & 31;
    const int warp = __shfl_sync(0xffffffffu, tid >> 5, 0);
    const int j = blockIdx.x >> 3, rank = blockIdx.x & 7;
    const int b = rank >> 2, split = rank & 3;
    const int pair = b * 16 + j;
    const int g = lane >> 2, t = lane & 3;
    const uint32_t sbase = smem_u32(smem);
    const uint32_t bar_full = sbase + kOffBar, bar_empty = bar_full + kItems * 8;
    const uint32_t bar_q = bar_empty + 2 * kTiles * 8, bar_stat = bar_q + 8;
    const uint32_t bar_qin = bar_stat + 8, bar_ml = bar_qin + 8, bar_c = bar_ml + 8, bar_k = bar_c + 8;
    Scratch* sc = &g_scratch;
    if (warp == kConsumerWarps) {
        const char* kbase = (const char*)kc + ((size_t)pair * kSK + (kSK - kW) + split * 64) * (kDH * 2);
        uint64_t pol;
        asm volatile("createpolicy.fractional.L2::evict_first.b64 %0, 1.0;" : "=l"(pol));
        if (lane == 0) {
            TS(0);
#pragma unroll
            for (int n = 0; n < kStart; n++) mbar_init(bar_full + n * 8, 1);
            asm volatile("fence.mbarrier_init.release.cluster;" ::: "memory");
#pragma unroll
            for (int n = 0; n < kStart; n++) {
                mbar_expect_tx(bar_full + n * 8, kTileBytes);
                bulk_g2s(sbase + kOffRing + n * kTileBytes, kbase + (size_t)n * (4 * kTileBytes), kTileBytes,
                         bar_full + n * 8, pol);
            }
#pragma unroll 1
            for (int n = kStart; n < kNumBars - 1; n++) mbar_init(bar_full + n * 8, 1);
            mbar_init(bar_k, kConsumerWarps);
            mbar_expect_tx(bar_qin, 2048);
            mbar_expect_tx(bar_ml, 128);
            mbar_expect_tx(bar_c, 8192);
            asm volatile("fence.mbarrier_init.release.cluster;" ::: "memory");
            asm volatile("prefetch.tensormap [%0];" ::"l"(&wo_map) : "memory");
            *(volatile uint32_t*)(smem + kOffMon) = 0xFFFFFFFFu;
            *(volatile uint32_t*)(smem + kOffMon + 4) = 0u;
        }
        __syncwarp();
        cluster_arrive();
        {
            const uint4 z = make_uint4(0, 0, 0, 0);
            float* rz = &sc->r[rank][j][0];
            st_rlx_v4(rz + lane * 4, z);
            if (lane < 4) st_rlx_v4(rz + 128 + lane * 4, z);
        }
        asm volatile("bar.arrive 2, 320;" ::: "memory");
        if (lane == 0) {
            const char* vbase = (const char*)vc + ((size_t)pair * kSK + (kSK - kW) + split * 64) * (kDH * 2) -
                                (size_t)kTiles * (4 * kTileBytes);
            int next = kStart;
            bool q_ready = false;
            int reported = 0;
#pragma unroll 1
            for (int m = 0; next < kItems; m++) {
                mbar_wait(bar_full + m * 8, 0, 1000 + m);
                if ((m & 3) == 0) TS(16 + m);
                if (!q_ready) q_ready = mbar_test(bar_q, 0);
                int win = q_ready ? (m >= K_END_AT ? K_END_WIN : kInflight) : kWin0;
                if (m < 2 * kTiles) {
                    asm volatile("red.relaxed.gpu.global.add.u32 [%0], 1;" ::"l"(&sc->landed) : "memory");
                    reported = m + 1;
                }
                if (q_ready) {
                    const uint32_t gl = *(volatile uint32_t*)(smem + kOffMon);
                    const int lag = (int)gl + K_BAL_BIAS - (m + 1) * 128;
                    if (gl != 0xFFFFFFFFu) win += (lag > K_BAL_HI2) ? 2 : (lag > K_BAL_HI1) ? 1 : (lag < -K_BAL_LO) ? -1 : 0;
                }
#pragma unroll 1
                while (next < kItems && next <= m + win) {
                    const int n = next++;
                    const uint32_t bar = bar_full + n * 8;
                    if (n < 2 * kTiles) {
                        if (n >= kNSlot) mbar_wait(bar_empty + (n - kNSlot) * 8, 0, 2000 + n);
                        mbar_expect_tx(bar, kTileBytes);
                        bulk_g2s(sbase + kOffRing + (n % kNSlot) * kTileBytes,
                                 (n < kTiles ? kbase : vbase) + (size_t)n * (4 * kTileBytes), kTileBytes, bar, pol);
                    } else {
                        const int part = n - 2 * kTiles;
                        if (part == 0) mbar_wait(bar_empty + 26 * 8, 0, 2600);
                        mbar_wait(bar_empty + (27 + part) * 8, 0, 2601);
                        mbar_expect_tx(bar, kWoBytes / kNWo);
                        tma_2d(sbase + kOffRing + kWoSlot * kTileBytes + part * (kWoBytes / kNWo), &wo_map, rank * kWoCols,
                               j * 256 + part * kWoRows, bar, pol);
                        if (n == kItems - 1) TS(1);
                    }
                }
            }
            *(volatile uint32_t*)(smem + kOffMon + 4) = 1u;
            asm volatile("red.relaxed.gpu.global.add.u32 [%0], %1;" ::"l"(&sc->landed), "r"(2 * kTiles - reported) : "memory");
        }
        return;
    }
    cluster_arrive();
    if (warp == kConsumerWarps + 1) {
        asm volatile("bar.sync 2, 320;" ::: "memory");
        cluster_wait();
        const uint32_t base = *(volatile uint32_t*)(smem + kOffX + 1156) * 4096u;
        const int hd = lane >> 4;
        int state = 0;
        uint32_t it = 0;
        while (true) {
            if (lane == 0) *(volatile uint32_t*)(smem + kOffMon) = ld_rlx_u32(&sc->landed) - base;
            if (state == 0 && __all_sync(0xffffffffu, mbar_test(bar_k, 0))) {
                const float2 v = *((const float2*)(smem + kOffML) + (lane & 15) * 2 + hd);
                float M = v.x;
#pragma unroll
                for (int o = 1; o < 16; o <<= 1) M = fmaxf(M, __shfl_xor_sync(0xffffffffu, M, o));
                float L = v.y * ex2(v.x - M);
#pragma unroll
                for (int o = 1; o < 16; o <<= 1) L += __shfl_xor_sync(0xffffffffu, L, o);
                if ((lane & 15) < 8)
                    st_async_u64(mapa(sbase + kOffML + 272 + (rank * 2 + hd) * 8, lane & 7),
                                 ((uint64_t)__float_as_uint(L) << 32) | __float_as_uint(M), mapa(bar_ml, lane & 7));
                state = 1;
            }
            if (state == 1 && __all_sync(0xffffffffu, mbar_test_cluster(bar_ml, 0))) {
                const uint64_t w = *(const uint64_t*)(smem + kOffML + 272 + ((b * 4 + (lane & 3)) * 2 + hd) * 8);
                const float Mi = __uint_as_float((uint32_t)w), Li = __uint_as_float((uint32_t)(w >> 32));
                float Mg = fmaxf(Mi, __shfl_xor_sync(0xffffffffu, Mi, 1));
                Mg = fmaxf(Mg, __shfl_xor_sync(0xffffffffu, Mg, 2));
                float Lg = Li * ex2(Mi - Mg);
                Lg += __shfl_xor_sync(0xffffffffu, Lg, 1);
                Lg += __shfl_xor_sync(0xffffffffu, Lg, 2);
                if ((lane & 15) == 0) *((float2*)(smem + kOffML + 256) + hd) = make_float2(Mg, 1.f / Lg);
                __syncwarp();
                if (lane == 0) mbar_arrive(bar_stat);
                state = 2;
            }
            if (state == 2 && __any_sync(0xffffffffu, *(volatile uint32_t*)(smem + kOffMon + 4) != 0u)) break;
            if (++it > kSpinLimit) SPIN_FAIL(105);
        }
        return;
    }
    uint32_t tag;
    unsigned char* const wscr = smem + kOffA + warp * 1024;
    {
        uint4 wv[9];
        uint32_t xb[9];
        uint4 xv = make_uint4(0, 0, 0, 0);
        uint32_t ep = 0;
        {
            const int row0 = (rank >> 2) * 288 + warp * 36 + t;
            const char* wp = (const char*)wq + ((size_t)row0 * 4096 + j * 256 + (rank & 3) * 64 + g * 8) * 2;
#pragma unroll
            for (int i = 0; i < 9; i++) wv[i] = ldg_stream128(wp + (size_t)i * (4 * 4096 * 2));
        }
        if (tid < 72) {
            const int bb = tid >= 36 ? 1 : 0;
            xv = ldg_stream128((const uint4*)(x + bb * kD + (rank >> 2) * 288) + (tid - bb * 36));
        } else if (tid == 96) {
            ep = ld_rlx_u32(&sc->epoch);
        }
        if (tid < 72) *(uint4*)(smem + kOffX + tid * 16) = xv;
        else if (tid == 96) *(uint2*)(smem + kOffX + 1152) = make_uint2(ep % 255u + 1u, ep);
        bar_consumers();
        if (tid == 0) TS(11);
        {
            const unsigned short* xs = (const unsigned short*)(smem + kOffX) + ((g >> 1) & 1) * 288 + warp * 36 + t;
#pragma unroll
            for (int i = 0; i < 9; i++) xb[i] = xs[4 * i];
            tag = *(const uint32_t*)(smem + kOffX + 1152);
        }
        float qa[4], qb[4];
        const int sh = (g & 1) * 16;
#pragma unroll
        for (int i = 0; i < 9; i++) xb[i] <<= sh;
        mma_bf16_z(qa, wv[0].x, wv[0].z, wv[1].x, wv[1].z, xb[0], xb[1]);
        mma_bf16_z(qb, wv[0].y, wv[0].w, wv[1].y, wv[1].w, xb[0], xb[1]);
#pragma unroll
        for (int u = 1; u < 4; u++) {
            mma_bf16(qa, wv[2 * u].x, wv[2 * u].z, wv[2 * u + 1].x, wv[2 * u + 1].z, xb[2 * u], xb[2 * u + 1]);
            mma_bf16(qb, wv[2 * u].y, wv[2 * u].w, wv[2 * u + 1].y, wv[2 * u + 1].w, xb[2 * u], xb[2 * u + 1]);
        }
        mma_bf16(qa, wv[8].x, wv[8].z, 0u, 0u, xb[8], 0u);
        mma_bf16(qb, wv[8].y, wv[8].w, 0u, 0u, xb[8], 0u);
        if (tid == 0) TS(2);
        if (t < 2) {
            float4* dst = (float4*)(wscr + 512 + t * 256 + g * 32);
            dst[0] = make_float4(qa[0], qa[1], qb[0], qb[1]);
            dst[1] = make_float4(qa[2], qa[3], qb[2], qb[3]);
        }
        asm volatile("bar.sync 2, 320;" ::: "memory");
        cluster_wait();
        if (tid < 128) {
            const float* pp = (const float*)(smem + kOffA + 512) + tid;
            float s0 = 0.f;
#pragma unroll
            for (int w = 0; w < 8; w++) s0 += pp[w * 256];
            const uint32_t dst = sbase + kOffQin + ((rank >> 2) * 256 + (rank & 3) * 64 + (tid & 63)) * 4;
            const int r0 = (tid >> 6) * 4;
#pragma unroll
            for (int s = 0; s < 4; s++) st_async_u32(mapa(dst, r0 + s), __float_as_uint(s0), mapa(bar_qin, r0 + s));
        }
        mbar_wait_cluster(bar_qin, 0, 101);
        {
            const float* qi = (const float*)(smem + kOffQin) + tid;
            ((__nv_bfloat16*)(smem + kOffQ))[tid] = __float2bfloat16(qi[0] + qi[256]);
        }
        bar_consumers();
        if (tid == 0) { mbar_arrive(bar_q); TS(3); }
    }
    uint4 qf[4];
#pragma unroll
    for (int i = 0; i < 4; i++)
        qf[i] = lds128(sbase + kOffQ + (g & 1) * 256 + (4 * (i ^ ((g >> 1) & 1)) + t) * 16);

    float m0 = 0.f, m1 = 0.f;
#pragma unroll 1
    for (int h = 0; h < 2; h++) {
        const int n = warp + 8 * h;
        mbar_wait(bar_full + n * 8, 0);
        const uint32_t kb = sbase + kOffRing + (n % kNSlot) * kTileBytes + g * 512 + t * 16;
        float s[4][4];
#pragma unroll
        for (int mt = 0; mt < 4; mt++) {
#pragma unroll
            for (int i = 0; i < 4; i++) {
                const uint32_t addr = kb + mt * 4096 + ((i ^ (g & 1)) * 64);
                const uint4 ra = lds128(addr), rb = lds128(addr + 256);
                if (i == 0) mma_bf16_z(s[mt], ra.x, rb.x, ra.y, rb.y, qf[i].x, qf[i].y);
                else mma_bf16(s[mt], ra.x, rb.x, ra.y, rb.y, qf[i].x, qf[i].y);
                mma_bf16(s[mt], ra.z, rb.z, ra.w, rb.w, qf[i].z, qf[i].w);
            }
        }
        __syncwarp();
        if (lane == 0) mbar_arrive(bar_empty + n * 8);
        const bool valid = ((t ^ g) & 1) == 0;
        const bool hi = t >= 2;
        float e0[4], e1[4];
        float m = -INFINITY;
#pragma unroll
        for (int i = 0; i < 4; i++) {
            e0[i] = valid ? (hi ? s[i][1] : s[i][0]) : -INFINITY;
            e1[i] = valid ? (hi ? s[i][3] : s[i][2]) : -INFINITY;
            m = fmaxf(m, fmaxf(e0[i], e1[i]));
        }
        m = fmaxf(m, __shfl_xor_sync(0xffffffffu, m, 1));
        m = fmaxf(m, __shfl_xor_sync(0xffffffffu, m, 4));
        m = fmaxf(m, __shfl_xor_sync(0xffffffffu, m, 8));
        m = fmaxf(m, __shfl_xor_sync(0xffffffffu, m, 16));
        const float mw = m * kScaleLog2;
        float l = 0.f;
        uint32_t* ps = (uint32_t*)(wscr + h * 256) + (t >> 1) * 32 + (g & 3) * 8 + (g >> 2);
#pragma unroll
        for (int i = 0; i < 4; i++) {
            const float p0 = ex2(fmaf(e0[i], kScaleLog2, -mw)), p1 = ex2(fmaf(e1[i], kScaleLog2, -mw));
            l += p0 + p1;
            if (valid) ps[2 * i] = pack_bf16(p0, p1);
        }
        l += __shfl_xor_sync(0xffffffffu, l, 1);
        l += __shfl_xor_sync(0xffffffffu, l, 4);
        l += __shfl_xor_sync(0xffffffffu, l, 8);
        l += __shfl_xor_sync(0xffffffffu, l, 16);
        if (lane == 0 || lane == 2) *((float2*)(smem + kOffML) + n * 2 + (t >> 1)) = make_float2(mw, l);
        if (h == 0) m0 = mw; else m1 = mw;
    }
    __syncwarp();
    if (lane == 0) mbar_arrive(bar_k);
    if (tid == 0) TS(4);
    m0 = __shfl_sync(0xffffffffu, m0, (lane & 28) + 2 * (t & 1));
    m1 = __shfl_sync(0xffffffffu, m1, (lane & 28) + 2 * (t & 1));

    float o[4][4];
    {
        const bool bval = (t & 1) == (g >> 2);
        const uint32_t sel0 = bval ? ((g & 1) ? 0x1044u : 0x4410u) : 0x4444u;
        const uint32_t sel1 = bval ? ((g & 1) ? 0x3244u : 0x4432u) : 0x4444u;
#pragma unroll 1
        for (int h = 0; h < 2; h++) {
            const uint32_t pa = sbase + kOffA + warp * 1024 + h * 256 + ((g >> 1) & 1) * 128 + t * 32;
            const uint4 pA = lds128(pa), pB = lds128(pa + 16);
            const uint32_t pw[8] = {pA.x, pA.y, pA.z, pA.w, pB.x, pB.y, pB.z, pB.w};
            const int n = kTiles + warp + 8 * h;
            float f1 = 0.f;
            if (h == 1) {
                mbar_wait(bar_stat, 0);
                const float2 st = *((const float2*)(smem + kOffML + 256) + (t & 1));
                const float f0 = ex2(m0 - st.x) * st.y;
                f1 = ex2(m1 - st.x) * st.y;
#pragma unroll
                for (int i = 0; i < 4; i++)
#pragma unroll
                    for (int c = 0; c < 4; c++) o[i][c] *= f0;
            }
            mbar_wait(bar_full + n * 8, 0);
            const uint32_t vb = sbase + kOffRing + (n % kNSlot) * kTileBytes + t * 512 + ((g ^ ((t & 1) * 4)) * 16);
            float acc[4][4];
#pragma unroll
            for (int r = 0; r < 8; r++) {
                const uint32_t addr = vb + r * 2048;
                const uint4 l0v = lds128(addr), l1v = lds128(addr + 128), l2v = lds128(addr + 256), l3v = lds128(addr + 384);
                const uint32_t b0 = __byte_perm(pw[r], 0, sel0), b1 = __byte_perm(pw[r], 0, sel1);
                if (r == 0) {
                    mma_bf16_z(acc[0], l0v.x, l1v.x, l2v.x, l3v.x, b0, b1);
                    mma_bf16_z(acc[1], l0v.y, l1v.y, l2v.y, l3v.y, b0, b1);
                    mma_bf16_z(acc[2], l0v.z, l1v.z, l2v.z, l3v.z, b0, b1);
                    mma_bf16_z(acc[3], l0v.w, l1v.w, l2v.w, l3v.w, b0, b1);
                } else {
                    mma_bf16(acc[0], l0v.x, l1v.x, l2v.x, l3v.x, b0, b1);
                    mma_bf16(acc[1], l0v.y, l1v.y, l2v.y, l3v.y, b0, b1);
                    mma_bf16(acc[2], l0v.z, l1v.z, l2v.z, l3v.z, b0, b1);
                    mma_bf16(acc[3], l0v.w, l1v.w, l2v.w, l3v.w, b0, b1);
                }
            }
            __syncwarp();
            if (lane == 0) mbar_arrive(bar_empty + n * 8);
#pragma unroll
            for (int i = 0; i < 4; i++)
#pragma unroll
                for (int c = 0; c < 4; c++) o[i][c] = h == 0 ? acc[i][c] : fmaf(f1, acc[i][c], o[i][c]);
        }
    }
    if (tid == 0) TS(5);
    {
        const bool v1 = t >= 2;
        float f[8];
#pragma unroll
        for (int i = 0; i < 4; i++) {
            f[2 * i] = (v1 ? o[i][2] : o[i][0]) + __shfl_xor_sync(0xffffffffu, v1 ? o[i][0] : o[i][2], 18);
            f[2 * i + 1] = (v1 ? o[i][3] : o[i][1]) + __shfl_xor_sync(0xffffffffu, v1 ? o[i][1] : o[i][3], 18);
        }
        float4* dst = (float4*)(wscr + (t & 1) * 512 + (v1 ? 256 : 0) + (g ^ (v1 ? 4 : 0)) * 32);
        dst[0] = make_float4(f[0], f[1], f[2], f[3]);
        dst[1] = make_float4(f[4], f[5], f[6], f[7]);
        bar_consumers();
        const float* rp = (const float*)(smem + kOffA) + tid;
        float a0 = 0.f, a1 = 0.f;
#pragma unroll
        for (int w = 0; w < 8; w += 2) {
            a0 += rp[w * 256];
            a1 += rp[w * 256 + 256];
        }
        const uint32_t val = __float_as_uint(a0 + a1);
        const uint32_t cdst = sbase + kOffC + (rank * 256 + tid) * 4;
#pragma unroll
        for (int r = 0; r < 8; r++) st_async_u32(mapa(cdst, r), val, mapa(bar_c, r));
    }
    if (tid == 0) TS(6);

    {
        uint4 wa[5][2];
        const uint32_t bar_wo = bar_full + (2 * kTiles + (warp * 32) / kWoRows) * 8;
        const uint32_t wbase = sbase + kOffRing + kWoSlot * kTileBytes +
                               (warp * 32 + (lane & 7) + ((lane >> 4) & 1) * 8) * (kWoCols * 2) + ((lane >> 3) & 1) * 16;
        mbar_wait_cluster(bar_c, 0, 102);
        if (tid == 0) TS(7);
        uint32_t bq[2][2];
        {
            const float2* ci = (const float2*)(smem + kOffC + (g & 1) * 4096) + warp * 16 + t;
#pragma unroll
            for (int ks = 0; ks < 2; ks++)
#pragma unroll
                for (int u = 0; u < 2; u++) {
                    const float2 c0 = ci[ks * 8 + u * 4], c1 = ci[128 + ks * 8 + u * 4];
                    const float2 c2 = ci[256 + ks * 8 + u * 4], c3 = ci[384 + ks * 8 + u * 4];
                    const uint32_t w = pack_bf16((c0.x + c1.x) + (c2.x + c3.x), (c0.y + c1.y) + (c2.y + c3.y));
                    bq[ks][u] = g < 2 ? w : 0u;
                }
        }
        mbar_wait(bar_wo, 0, 3000);
        if (tid == 0) TS(8);
#pragma unroll
        for (int mt = 0; mt < 5; mt++) {
            wa[mt][0] = ldsm_x4_trans(wbase + mt * 32);
            wa[mt][1] = ldsm_x4_trans(wbase + 16 * (kWoCols * 2) + mt * 32);
        }
        float acc[5][4];
#pragma unroll
        for (int mt = 0; mt < 5; mt++) {
            mma_bf16_z(acc[mt], wa[mt][0].x, wa[mt][0].y, wa[mt][0].z, wa[mt][0].w, bq[0][0], bq[0][1]);
            mma_bf16(acc[mt], wa[mt][1].x, wa[mt][1].y, wa[mt][1].z, wa[mt][1].w, bq[1][0], bq[1][1]);
        }
        if (t == 0) {
            float2* part = (float2*)wscr;
#pragma unroll
            for (int mt = 0; mt < 5; mt++) {
                part[mt * 16 + g] = make_float2(acc[mt][0], acc[mt][1]);
                part[mt * 16 + g + 8] = make_float2(acc[mt][2], acc[mt][3]);
            }
        }
        bar_consumers();
        if (tid < 144) {
            const int bb = tid >= 72 ? 1 : 0, col = tid - bb * 72;
            const float* pp = (const float*)(smem + kOffA) + col * 2 + bb;
            float s0 = 0.f, s1 = 0.f;
#pragma unroll
            for (int w = 0; w < 8; w += 2) {
                s0 += pp[w * 256];
                s1 += pp[w * 256 + 256];
            }
            st_rlx_u32(&sc->r[rank][j][tid], tag_f32(s0 + s1, tag));
        }
        if (tid == 0) TS(9);
        if (warp >= 5 && j < 9) {
            const int pq8 = lane >> 2;
            const float* rsrc = &sc->r[rank][pq8][j * 16 + (lane & 3) * 4];
            if (warp > 5) { const long long c0 = clock64(); while (clock64() - c0 < (warp - 5) * 110) {} }
            uint4 w0 = ld_rlx_v4(rsrc), w1 = ld_rlx_v4(rsrc + 8 * 144);
            uint32_t it = 0;
            while (true) {
                const bool ok0 = tagged4(w0, tag), ok1 = tagged4(w1, tag);
                if (__all_sync(0xffffffffu, ok0 && ok1)) break;
                if (!ok0) w0 = ld_rlx_v4(rsrc);
                if (!ok1) w1 = ld_rlx_v4(rsrc + 8 * 144);
                if (++it > kSpinLimit) SPIN_FAIL(103);
            }
            const float x0 = untag(w0.x) + untag(w1.x), x1 = untag(w0.y) + untag(w1.y);
            const float x2 = untag(w0.z) + untag(w1.z), x3 = untag(w0.w) + untag(w1.w);
            const bool h2 = pq8 >= 4, h1 = (pq8 & 2) != 0;
            const float y0 = (h2 ? x2 : x0) + __shfl_xor_sync(0xffffffffu, h2 ? x0 : x2, 16);
            const float y1 = (h2 ? x3 : x1) + __shfl_xor_sync(0xffffffffu, h2 ? x1 : x3, 16);
            float z = (h1 ? y1 : y0) + __shfl_xor_sync(0xffffffffu, h1 ? y0 : y1, 8);
            z += __shfl_xor_sync(0xffffffffu, z, 4);
            if ((pq8 & 1) == 0) {
                const int e = j * 16 + (lane & 3) * 4 + (h2 ? 2 : 0) + (h1 ? 1 : 0);
                const int bb = e >= 72 ? 1 : 0;
                out[bb * kD + rank * kWoCols + (e - bb * 72)] = __float2bfloat16(z);
            }
            if (blockIdx.x == 0 && warp == 5 && lane == 0)
                asm volatile("red.relaxed.gpu.global.add.u32 [%0], 1;" ::"l"(&sc->epoch) : "memory");
            if (warp == 5 && lane == 0) TS(10);
        }
    }
}

}

typedef CUresult (*EncodeTiledFn)(CUtensorMap*, CUtensorMapDataType, cuuint32_t, void*, const cuuint64_t*,
                                  const cuuint64_t*, const cuuint32_t*, const cuuint32_t*, CUtensorMapInterleave,
                                  CUtensorMapSwizzle, CUtensorMapL2promotion, CUtensorMapFloatOOBfill);

extern "C" void kernel_launch(void* const* d_in, const int* in_sizes, int n_in, void* d_out, int out_size) {
    (void)in_sizes; (void)n_in; (void)out_size;
    static EncodeTiledFn encode = nullptr;
    if (!encode) {
        void* fn = nullptr;
        cudaDriverEntryPointQueryResult st;
        cudaGetDriverEntryPoint("cuTensorMapEncodeTiled", &fn, cudaEnableDefault, &st);
        encode = (EncodeTiledFn)fn;
        cudaFuncSetAttribute(decode_attn_kernel, cudaFuncAttributeMaxDynamicSharedMemorySize, kSmemBytes);
    }
    CUtensorMap wo_map;
    const cuuint64_t dims[2] = {(cuuint64_t)kD, 4096};
    const cuuint64_t strides[1] = {(cuuint64_t)kD * 2};
    const cuuint32_t box[2] = {(cuuint32_t)kWoCols, (cuuint32_t)kWoRows};
    const cuuint32_t estr[2] = {1, 1};
    encode(&wo_map, CU_TENSOR_MAP_DATA_TYPE_BFLOAT16, 2, d_in[4], dims, strides, box, estr,
           CU_TENSOR_MAP_INTERLEAVE_NONE, CU_TENSOR_MAP_SWIZZLE_NONE, CU_TENSOR_MAP_L2_PROMOTION_L2_256B,
           CU_TENSOR_MAP_FLOAT_OOB_FILL_NONE);
    decode_attn_kernel<<<kNCTA, kThreads, kSmemBytes, cudaStreamPerThread>>>(
        (const __nv_bfloat16*)d_in[0], (const __nv_bfloat16*)d_in[1], (const __nv_bfloat16*)d_in[2],
        (const __nv_bfloat16*)d_in[3], wo_map, (__nv_bfloat16*)d_out);
}
```

```cpp
#include <cuda_runtime.h>
#include <cuda.h>
#include <cuda_bf16.h>
#include <stdint.h>

namespace {

constexpr int kD = 576, kSK = 32768, kDH = 128, kW = 4096;
constexpr int kNCTA = 128;
constexpr int kConsumerWarps = 8;
constexpr int kThreads = 320;
constexpr int kTileBytes = 16384;
constexpr int kNSlot = 6;
constexpr int kInflight = 4;
constexpr int kStart = 3;
constexpr int kWin0 = 3;
constexpr int kBalBias = 120;
constexpr int kBalRate = 112;
constexpr int kBalBehind1 = 64, kBalBehind2 = 192, kBalAhead = 128;
constexpr int kTiles = 16;
constexpr int kNWo = 4;
constexpr int kWoRows = 128 / kNWo;
constexpr int kWoCols = 72;
constexpr int kWoBytes = 256 * kWoCols * 2;
constexpr int kWoSlot = 2;
constexpr int kItems = 2 * kTiles + kNWo;

constexpr int kOffRing = 0;
constexpr int kOffA = kOffRing + kNSlot * kTileBytes;
constexpr int kOffC = kOffA + 8192;
constexpr int kOffQin = kOffC;
constexpr int kOffX = kOffC + 2048;
constexpr int kOffQ = kOffC + 3328;
constexpr int kOffML = kOffC + 8192;
constexpr int kOffMon = kOffML + 256 + 16 + 128;
constexpr int kNumEmpty = 29;
constexpr int kNumFull = 2 * kTiles;
constexpr int kNumBars = kNumFull + kNumEmpty + 8;
constexpr int kWqSlot = 3;
constexpr int kOffBar = kOffMon + 16;
constexpr int kSmemBytes = kOffBar + kNumBars * 8;

constexpr float kScale = 0.08838834764831845f;
constexpr float kLog2e = 1.4426950408889634f;
constexpr uint32_t kSpinLimit = 1u << 22;

struct __align__(1024) Scratch {
    float r[8][16][144];
    unsigned landed;
};
__device__ Scratch g_scratch;

static_assert(kSmemBytes <= 115712, "two CTAs per SM");

#define SPIN_FAIL() __trap()

__device__ __forceinline__ uint32_t smem_u32(const void* p) { return (uint32_t)__cvta_generic_to_shared(p); }
__device__ __forceinline__ void mbar_init(uint32_t bar, uint32_t cnt) {
    asm volatile("mbarrier.init.shared::cta.b64 [%0], %1;" ::"r"(bar), "r"(cnt) : "memory");
}
__device__ __forceinline__ void mbar_expect_tx(uint32_t bar, uint32_t bytes) {
    asm volatile("mbarrier.arrive.expect_tx.shared::cta.b64 _, [%0], %1;" ::"r"(bar), "r"(bytes) : "memory");
}
__device__ __forceinline__ void mbar_arrive(uint32_t bar) {
    asm volatile("mbarrier.arrive.shared::cta.b64 _, [%0];" ::"r"(bar) : "memory");
}
__device__ __forceinline__ bool mbar_try(uint32_t bar, uint32_t parity) {
    uint32_t done;
    asm volatile(
        "{\n.reg .pred p;\n"
        "mbarrier.try_wait.parity.shared::cta.b64 p, [%1], %2;\n"
        "selp.u32 %0, 1, 0, p;\n}"
        : "=r"(done) : "r"(bar), "r"(parity) : "memory");
    return done != 0;
}
__device__ __forceinline__ void mbar_wait(uint32_t bar, uint32_t parity) {
    uint32_t it = 0;
    while (!mbar_try(bar, parity))
        if (++it > kSpinLimit) SPIN_FAIL();
}
__device__ __forceinline__ bool mbar_test(uint32_t bar, uint32_t parity) {
    uint32_t done;
    asm volatile(
        "{\n.reg .pred p;\n"
        "mbarrier.test_wait.parity.shared::cta.b64 p, [%1], %2;\n"
        "selp.u32 %0, 1, 0, p;\n}"
        : "=r"(done) : "r"(bar), "r"(parity) : "memory");
    return done != 0;
}
__device__ __forceinline__ uint32_t clock32() {
    uint32_t c;
    asm volatile("mov.u32 %0, %clock;" : "=r"(c));
    return c;
}
__device__ __forceinline__ uint32_t mapa(uint32_t addr, uint32_t rank) {
    uint32_t r;
    asm("mapa.shared::cluster.u32 %0, %1, %2;" : "=r"(r) : "r"(addr), "r"(rank));
    return r;
}
__device__ __forceinline__ void st_async_u32(uint32_t raddr, uint32_t v, uint32_t rbar) {
    asm volatile("st.async.weak.shared::cluster.mbarrier::complete_tx::bytes.u32 [%0], %1, [%2];"
                 ::"r"(raddr), "r"(v), "r"(rbar) : "memory");
}
__device__ __forceinline__ void st_async_u64(uint32_t raddr, uint64_t v, uint32_t rbar) {
    asm volatile("st.async.weak.shared::cluster.mbarrier::complete_tx::bytes.u64 [%0], %1, [%2];"
                 ::"r"(raddr), "l"(v), "r"(rbar) : "memory");
}
__device__ __forceinline__ void cluster_arrive() { asm volatile("barrier.cluster.arrive.relaxed.aligned;" ::: "memory"); }
__device__ __forceinline__ void cluster_wait() { asm volatile("barrier.cluster.wait.acquire.aligned;" ::: "memory"); }
__device__ __forceinline__ void bulk_g2s(uint32_t dst, const void* src, uint32_t bytes, uint32_t bar, uint64_t pol) {
    asm volatile(
        "cp.async.bulk.shared::cluster.global.mbarrier::complete_tx::bytes.L2::cache_hint [%0], [%1], %2, [%3], %4;"
        ::"r"(dst), "l"(src), "r"(bytes), "r"(bar), "l"(pol) : "memory");
}
__device__ __forceinline__ void tma_3d(uint32_t dst, const CUtensorMap* map, int c0, int c1, int c2, uint32_t bar, uint64_t pol) {
    asm volatile(
        "cp.async.bulk.tensor.3d.shared::cluster.global.mbarrier::complete_tx::bytes.L2::cache_hint"
        " [%0], [%1, {%3, %4, %5}], [%2], %6;"
        ::"r"(dst), "l"(map), "r"(bar), "r"(c0), "r"(c1), "r"(c2), "l"(pol) : "memory");
}
__device__ __forceinline__ void tma_2d(uint32_t dst, const CUtensorMap* map, int c0, int c1, uint32_t bar, uint64_t pol) {
    asm volatile(
        "cp.async.bulk.tensor.2d.shared::cluster.global.mbarrier::complete_tx::bytes.L2::cache_hint"
        " [%0], [%1, {%3, %4}], [%2], %5;"
        ::"r"(dst), "l"(map), "r"(bar), "r"(c0), "r"(c1), "l"(pol) : "memory");
}
__device__ __forceinline__ void st_async_v4(uint32_t raddr, float a, float b, float c, float d, uint32_t rbar) {
    asm volatile("st.async.weak.shared::cluster.mbarrier::complete_tx::bytes.v4.f32 [%0], {%1,%2,%3,%4}, [%5];"
                 ::"r"(raddr), "f"(a), "f"(b), "f"(c), "f"(d), "r"(rbar) : "memory");
}
__device__ __forceinline__ uint4 ldsm_x4_trans(uint32_t addr) {
    uint4 v;
    asm volatile("ldmatrix.sync.aligned.m8n8.x4.trans.shared.b16 {%0,%1,%2,%3}, [%4];"
                 : "=r"(v.x), "=r"(v.y), "=r"(v.z), "=r"(v.w) : "r"(addr) : "memory");
    return v;
}
__device__ __forceinline__ uint4 lds128(uint32_t addr) {
    uint4 v;
    asm volatile("ld.shared.v4.u32 {%0,%1,%2,%3}, [%4];" : "=r"(v.x), "=r"(v.y), "=r"(v.z), "=r"(v.w) : "r"(addr));
    return v;
}
__device__ __forceinline__ float ldsf(uint32_t addr) {
    float v;
    asm volatile("ld.shared.f32 %0, [%1];" : "=f"(v) : "r"(addr));
    return v;
}
__device__ __forceinline__ void pin(uint32_t& v) { asm volatile("" : "+r"(v)); }
template <class T> __device__ __forceinline__ void pin(T*& p) { asm volatile("" : "+l"(p)); }
__device__ __forceinline__ void mma_bf16(float (&c)[4], uint32_t a0, uint32_t a1, uint32_t a2, uint32_t a3,
                                         uint32_t b0, uint32_t b1) {
    asm volatile(
        "mma.sync.aligned.m16n8k16.row.col.f32.bf16.bf16.f32 {%0,%1,%2,%3}, {%4,%5,%6,%7}, {%8,%9}, {%0,%1,%2,%3};"
        : "+f"(c[0]), "+f"(c[1]), "+f"(c[2]), "+f"(c[3])
        : "r"(a0), "r"(a1), "r"(a2), "r"(a3), "r"(b0), "r"(b1));
}
__device__ __forceinline__ void mma_bf16_z(float (&c)[4], uint32_t a0, uint32_t a1, uint32_t a2, uint32_t a3,
                                           uint32_t b0, uint32_t b1) {
    asm volatile(
        "mma.sync.aligned.m16n8k16.row.col.f32.bf16.bf16.f32 {%0,%1,%2,%3}, {%4,%5,%6,%7}, {%8,%9}, {%10,%10,%10,%10};"
        : "=f"(c[0]), "=f"(c[1]), "=f"(c[2]), "=f"(c[3])
        : "r"(a0), "r"(a1), "r"(a2), "r"(a3), "r"(b0), "r"(b1), "f"(0.f));
}
__device__ __forceinline__ uint32_t ld_rlx_u32(const void* p) {
    uint32_t v;
    asm volatile("ld.relaxed.gpu.global.u32 %0, [%1];" : "=r"(v) : "l"(p) : "memory");
    return v;
}
__device__ __forceinline__ uint4 ld_rlx_v4(const void* p) {
    uint4 v;
    asm volatile("ld.relaxed.gpu.global.v4.u32 {%0,%1,%2,%3}, [%4];"
                 : "=r"(v.x), "=r"(v.y), "=r"(v.z), "=r"(v.w) : "l"(p) : "memory");
    return v;
}
__device__ __forceinline__ void st_rlx_v4(void* p, uint4 v) {
    asm volatile("st.relaxed.gpu.global.v4.u32 [%0], {%1,%2,%3,%4};" ::"l"(p), "r"(v.x), "r"(v.y), "r"(v.z), "r"(v.w)
                 : "memory");
}
__device__ __forceinline__ uint4 ldg_stream128(const void* p) {
    uint4 v;
    asm volatile("ld.global.nc.L1::no_allocate.v4.u32 {%0,%1,%2,%3}, [%4];"
                 : "=r"(v.x), "=r"(v.y), "=r"(v.z), "=r"(v.w) : "l"(p));
    return v;
}
__device__ __forceinline__ void bar_consumers() { asm volatile("bar.sync 1, 256;" ::: "memory"); }
__device__ __forceinline__ uint32_t tag_f32(float v, uint32_t tag) { return (__float_as_uint(v) & ~0xFFu) | tag; }
__device__ __forceinline__ bool tagged4(const uint4& v, uint32_t tag) {
    return ((((v.x ^ tag) | (v.y ^ tag)) | ((v.z ^ tag) | (v.w ^ tag))) & 0xFFu) == 0;
}
__device__ __forceinline__ float untag(uint32_t v) { return __uint_as_float(v & ~0xFFu); }
__device__ __forceinline__ uint32_t pack_bf16(float lo, float hi) {
    uint32_t r;
    asm("cvt.rn.bf16x2.f32 %0, %1, %2;" : "=r"(r) : "f"(hi), "f"(lo));
    return r;
}
__device__ __forceinline__ float ex2(float x) {
    float y;
    asm("ex2.approx.ftz.f32 %0, %1;" : "=f"(y) : "f"(x));
    return y;
}

__global__ void __cluster_dims__(8, 1, 1) __launch_bounds__(kThreads, 2)
decode_attn_kernel(const __nv_bfloat16* __restrict__ x, const __nv_bfloat16* __restrict__ kc,
                   __nv_bfloat16* __restrict__ out, const __grid_constant__ CUtensorMap wq_map,
                   const __grid_constant__ CUtensorMap v_map, const __grid_constant__ CUtensorMap wo_map) {
    extern __shared__ __align__(1024) unsigned char smem[];
    int tid, cta;
    asm volatile("mov.u32 %0, %tid.x;" : "=r"(tid));
    asm volatile("mov.u32 %0, %ctaid.x;" : "=r"(cta));
    const int lane = tid & 31;
    const int warp = __shfl_sync(0xffffffffu, tid >> 5, 0);
    const int j = cta >> 3, rank = cta & 7;
    const int b = rank >> 2, split = rank & 3;
    const int pair = b * 16 + j;
    const int g = lane >> 2, t = lane & 3;
    const uint32_t sbase = smem_u32(smem);
    const uint32_t bar_full = sbase + kOffBar, bar_empty = bar_full + kNumFull * 8;
    const uint32_t bar_q = bar_empty + kNumEmpty * 8, bar_stat = bar_q + 8;
    const uint32_t bar_qin = bar_stat + 8, bar_ml = bar_qin + 8, bar_c = bar_ml + 8;
    const uint32_t bar_wq = bar_c + 8, bar_wqf = bar_wq + 8, bar_k = bar_wqf + 8;
    Scratch* sc = &g_scratch;
    if (warp == kConsumerWarps) {
        const char* kbase = (const char*)kc + ((size_t)pair * kSK + (kSK - kW) + split * 64) * (kDH * 2);
        uint64_t pol;
        asm volatile("createpolicy.fractional.L2::evict_first.b64 %0, 1.0;" : "=l"(pol));
        if (lane == 0) {
            asm volatile("prefetch.tensormap [%0];" ::"l"(&wq_map) : "memory");
            if (sbase & 1023u) __trap();
#pragma unroll
            for (int n = 0; n < kStart; n++) mbar_init(bar_full + n * 8, 1);
            mbar_init(bar_wq, 1);
            asm volatile("fence.mbarrier_init.release.cluster;" ::: "memory");
            mbar_expect_tx(bar_wq, 288 * 128);
#pragma unroll
            for (int h = 0; h < 2; h++)
                tma_2d(sbase + kOffRing + kWqSlot * kTileBytes + h * (144 * 128), &wq_map, j * 256 + (rank & 3) * 64,
                       (rank >> 2) * 288 + h * 144, bar_wq, pol);
#pragma unroll
            for (int n = 0; n < kStart; n++) {
                mbar_expect_tx(bar_full + n * 8, kTileBytes);
                bulk_g2s(sbase + kOffRing + n * kTileBytes, kbase + (size_t)n * (4 * kTileBytes), kTileBytes,
                         bar_full + n * 8, pol);
            }
#pragma unroll 1
            for (int n = kStart; n < kNumBars - 3; n++)
                mbar_init(bar_full + n * 8, n >= kNumFull + kTiles && n < kNumFull + kNumEmpty ? kConsumerWarps : 1);
            mbar_init(bar_wqf, kConsumerWarps);
            mbar_init(bar_k, kConsumerWarps);
            mbar_expect_tx(bar_qin, 2048);
            mbar_expect_tx(bar_ml, 128);
            mbar_expect_tx(bar_c, 8192);
            asm volatile("fence.mbarrier_init.release.cluster;" ::: "memory");
            asm volatile("prefetch.tensormap [%0];" ::"l"(&v_map) : "memory");
            asm volatile("prefetch.tensormap [%0];" ::"l"(&wo_map) : "memory");
            *(volatile uint32_t*)(smem + kOffMon) = 0xFFFFFFFFu;
            *(volatile uint32_t*)(smem + kOffMon + 8) = 0u;
        }
        __syncwarp();
        cluster_arrive();
        {
            const uint4 z = make_uint4(0, 0, 0, 0);
            float* rz = &sc->r[rank][j][0];
            st_rlx_v4(rz + lane * 4, z);
            if (lane < 4) st_rlx_v4(rz + 128 + lane * 4, z);
        }
        asm volatile("bar.arrive 2, 320;" ::: "memory");
        if (lane == 0) {
            const int vrow = pair * kSK + (kSK - kW) + split * 64 - kTiles * 256;
            int next = kStart;
            bool q_ready = false;
            int reported = 0;
#pragma unroll 1
            for (int m = 0; next < kItems; m++) {
                mbar_wait(bar_full + m * 8, 0);
                if (!q_ready) q_ready = mbar_test(bar_q, 0);
                int win = q_ready ? kInflight : kWin0;
                if (m < 2 * kTiles) {
                    asm volatile("red.relaxed.gpu.global.add.u32 [%0], 1;" ::"l"(&sc->landed) : "memory");
                    reported = m + 1;
                }
                if (q_ready) {
                    const unsigned long long gt = *(volatile unsigned long long*)(smem + kOffMon);
                    const uint32_t gl = (uint32_t)gt;
                    const int age = (int)(clock32() - (uint32_t)(gt >> 32));
                    const int lag = (int)gl + ((age * kBalRate) >> 10) + kBalBias - (m + 1) * 128;
                    if (gl != 0xFFFFFFFFu) win += (lag > kBalBehind2) ? 2 : (lag > kBalBehind1) ? 1 : (lag < -kBalAhead) ? -1 : 0;
                }
#pragma unroll 1
                while (next < kItems && ((next < 2 * kTiles ? next : 2 * kTiles + 1 + (next - 2 * kTiles) / 2) <= m + win ||
                                         m >= 2 * kTiles - 1)) {
                    const int n = next++;
                    const uint32_t bar = bar_full + n * 8;
                    if (n < 2 * kTiles) {
                        if (n >= kNSlot) mbar_wait(bar_empty + (n - kNSlot) * 8, 0);
                        else mbar_wait(bar_wqf, 0);
                        mbar_expect_tx(bar, kTileBytes);
                        const uint32_t dst = sbase + kOffRing + (n % kNSlot) * kTileBytes;
                        if (n < kTiles) bulk_g2s(dst, kbase + (size_t)n * (4 * kTileBytes), kTileBytes, bar, pol);
                        else tma_3d(dst, &v_map, 0, vrow + n * 256, 0, bar, pol);
                    } else {
                        const int part = n - 2 * kTiles;
                        mbar_wait(bar_empty + (26 + (part * (kWoBytes / kNWo)) / kTileBytes) * 8, 0);
                        mbar_wait(bar_empty + (26 + ((part + 1) * (kWoBytes / kNWo) - 1) / kTileBytes) * 8, 0);
                        mbar_expect_tx(bar_full + part * 8, kWoBytes / kNWo);
                        tma_3d(sbase + kOffRing + kWoSlot * kTileBytes + part * (kWoBytes / kNWo), &wo_map, rank * kWoCols,
                               part * kWoRows, 2 * j, bar_full + part * 8, pol);
                    }
                }
            }
            *(volatile uint32_t*)(smem + kOffMon + 8) = 1u;
            asm volatile("red.relaxed.gpu.global.add.u32 [%0], %1;" ::"l"(&sc->landed), "r"(2 * kTiles - reported) : "memory");
        }
        return;
    }
    cluster_arrive();
    if (warp == kConsumerWarps + 1) {
        asm volatile("bar.sync 2, 320;" ::: "memory");
        cluster_wait();
        const uint32_t base = *(volatile uint32_t*)(smem + kOffX + 1156) * 4096u;
        const int hd = lane >> 4;
        int state = 0;
        float Mc = 0.f;
        uint32_t it = 0;
        while (true) {
            if (lane == 0) {
                const uint32_t c0 = clock32();
                const uint32_t gl = ld_rlx_u32(&sc->landed) - base;
                uint32_t c1;
                asm volatile("{ .reg .u32 d; and.b32 d, %1, 0; mov.u32 %0, %clock; add.u32 %0, %0, d; }" : "=r"(c1) : "r"(gl) : "memory");
                *(volatile unsigned long long*)(smem + kOffMon) = ((unsigned long long)(c0 + ((c1 - c0) >> 1)) << 32) | gl;
            }
            if (state == 0 && __all_sync(0xffffffffu, mbar_test(bar_k, 0))) {
                const float2 v = *((const float2*)(smem + kOffML) + (lane & 15) * 2 + hd);
                float M = v.x;
#pragma unroll
                for (int o = 1; o < 16; o <<= 1) M = fmaxf(M, __shfl_xor_sync(0xffffffffu, M, o));
                float L = v.y * ex2(v.x - M);
#pragma unroll
                for (int o = 1; o < 16; o <<= 1) L += __shfl_xor_sync(0xffffffffu, L, o);
                Mc = M;
                if ((lane & 15) < 8)
                    st_async_u64(mapa(sbase + kOffML + 272 + (rank * 2 + hd) * 8, lane & 7),
                                 ((uint64_t)__float_as_uint(L) << 32) | __float_as_uint(M), mapa(bar_ml, lane & 7));
                state = 1;
            }
            if (state == 1 && __all_sync(0xffffffffu, mbar_test(bar_ml, 0))) {
                const uint64_t w = *(const uint64_t*)(smem + kOffML + 272 + ((b * 4 + (lane & 3)) * 2 + hd) * 8);
                const float Mi = __uint_as_float((uint32_t)w), Li = __uint_as_float((uint32_t)(w >> 32));
                float Mg = fmaxf(Mi, __shfl_xor_sync(0xffffffffu, Mi, 1));
                Mg = fmaxf(Mg, __shfl_xor_sync(0xffffffffu, Mg, 2));
                float Lg = Li * ex2(Mi - Mg);
                Lg += __shfl_xor_sync(0xffffffffu, Lg, 1);
                Lg += __shfl_xor_sync(0xffffffffu, Lg, 2);
                if ((lane & 15) == 0) *((float*)(smem + kOffML + 256) + hd) = ex2(Mc - Mg) / Lg;
                __syncwarp();
                if (lane == 0) mbar_arrive(bar_stat);
                state = 2;
            }
            if (state == 2 && __any_sync(0xffffffffu, *(volatile uint32_t*)(smem + kOffMon + 8) != 0u)) break;
            if (++it > kSpinLimit) SPIN_FAIL();
        }
        return;
    }
    uint32_t tag;
    unsigned char* const wscr = smem + kOffA + warp * 1024;
    {
        uint4 wv[9];
        uint32_t xb[9];
        if (tid < 72) {
            const int bb = tid >= 36 ? 1 : 0;
            *(uint4*)(smem + kOffX + tid * 16) =
                ldg_stream128((const uint4*)(x + bb * kD + (rank >> 2) * 288) + (tid - bb * 36));
        } else if (tid == 96) {
            const uint32_t ep = ld_rlx_u32(&sc->landed) >> 12;
            *(uint2*)(smem + kOffX + 1152) = make_uint2(ep % 255u + 1u, ep);
        }
        asm volatile("bar.sync 2, 320;" ::: "memory");
        {
            const unsigned short* xs = (const unsigned short*)(smem + kOffX) + ((g >> 1) & 1) * 288 + warp * 36;
#pragma unroll
            for (int i = 0; i < 8; i++) xb[i] = xs[2 * t + (i & 1) + 8 * (i >> 1)];
            xb[8] = xs[32 + t];
            tag = *(const uint32_t*)(smem + kOffX + 1152);
        }
        mbar_wait(bar_wq, 0);
#pragma unroll
        for (int i = 0; i < 9; i++) {
            const int r = warp * 36 + (i < 8 ? 2 * t + (i & 1) + 8 * (i >> 1) : 32 + t);
            wv[i] = lds128(sbase + kOffRing + kWqSlot * kTileBytes + r * 128 + ((g ^ (r & 7)) * 16));
        }
        float qa[4], qb[4];
        const int sh = (g & 1) * 16;
#pragma unroll
        for (int i = 0; i < 9; i++) xb[i] <<= sh;
        mma_bf16_z(qa, wv[0].x, wv[0].z, wv[1].x, wv[1].z, xb[0], xb[1]);
        mma_bf16_z(qb, wv[0].y, wv[0].w, wv[1].y, wv[1].w, xb[0], xb[1]);
#pragma unroll
        for (int u = 1; u < 4; u++) {
            mma_bf16(qa, wv[2 * u].x, wv[2 * u].z, wv[2 * u + 1].x, wv[2 * u + 1].z, xb[2 * u], xb[2 * u + 1]);
            mma_bf16(qb, wv[2 * u].y, wv[2 * u].w, wv[2 * u + 1].y, wv[2 * u + 1].w, xb[2 * u], xb[2 * u + 1]);
        }
        mma_bf16(qa, wv[8].x, wv[8].z, 0u, 0u, xb[8], 0u);
        mma_bf16(qb, wv[8].y, wv[8].w, 0u, 0u, xb[8], 0u);
        __syncwarp();
        if (lane == 0) mbar_arrive(bar_wqf);
        if (t < 2) {
            float4* dst = (float4*)(wscr + 512 + t * 256 + g * 32);
            dst[0] = make_float4(qa[0], qa[1], qb[0], qb[1]);
            dst[1] = make_float4(qa[2], qa[3], qb[2], qb[3]);
        }
        bar_consumers();
        cluster_wait();
        if (tid < 128) {
            const float* pp = (const float*)(smem + kOffA + 512) + tid;
            float s0 = 0.f;
#pragma unroll
            for (int w = 0; w < 8; w++) s0 += pp[w * 256];
            const uint32_t dst = sbase + kOffQin + ((rank >> 2) * 256 + (rank & 3) * 64 + (tid & 63)) * 4;
            const int r0 = (tid >> 6) * 4;
#pragma unroll
            for (int s = 0; s < 4; s++) st_async_u32(mapa(dst, r0 + s), __float_as_uint(s0), mapa(bar_qin, r0 + s));
        }
        mbar_wait(bar_qin, 0);
        {
            const float* qi = (const float*)(smem + kOffQin) + tid;
            ((__nv_bfloat16*)(smem + kOffQ))[tid] = __float2bfloat16(qi[0] + qi[256]);
        }
        bar_consumers();
        if (tid == 0) mbar_arrive(bar_q);
    }
    uint4 qf[4];
#pragma unroll
    for (int i = 0; i < 4; i++)
        qf[i] = lds128(sbase + kOffQ + (g & 1) * 256 + (4 * (i ^ ((g >> 1) & 1)) + t) * 16);

#pragma unroll 1
    for (int h = 0; h < 2; h++) {
        const int n = warp + 8 * h;
        mbar_wait(bar_full + n * 8, 0);
        const uint32_t kb = sbase + kOffRing + (n % kNSlot) * kTileBytes + g * 512 + t * 16;
        float s[4][4];
#pragma unroll
        for (int mt = 0; mt < 4; mt++) {
#pragma unroll
            for (int i = 0; i < 4; i++) {
                const uint32_t addr = kb + mt * 4096 + ((i ^ (g & 1)) * 64);
                const uint4 ra = lds128(addr), rb = lds128(addr + 256);
                if (i == 0) mma_bf16_z(s[mt], ra.x, rb.x, ra.y, rb.y, qf[i].x, qf[i].y);
                else mma_bf16(s[mt], ra.x, rb.x, ra.y, rb.y, qf[i].x, qf[i].y);
                mma_bf16(s[mt], ra.z, rb.z, ra.w, rb.w, qf[i].z, qf[i].w);
            }
        }
        __syncwarp();
        if (lane == 0) mbar_arrive(bar_empty + n * 8);
        const bool valid = ((t ^ g) & 1) == 0;
        const bool hi = t >= 2;
        float e0[4], e1[4];
        float m = -INFINITY;
#pragma unroll
        for (int i = 0; i < 4; i++) {
            e0[i] = valid ? (hi ? s[i][1] : s[i][0]) : -INFINITY;
            e1[i] = valid ? (hi ? s[i][3] : s[i][2]) : -INFINITY;
            uint32_t r = pack_bf16(e0[i], e1[i]);
            r = pack_bf16(__uint_as_float(r << 16) * kScale, __uint_as_float(r & 0xFFFF0000u) * kScale);
            e0[i] = __uint_as_float(r << 16);
            e1[i] = __uint_as_float(r & 0xFFFF0000u);
            m = fmaxf(m, fmaxf(e0[i], e1[i]));
        }
        m = fmaxf(m, __shfl_xor_sync(0xffffffffu, m, 1));
        m = fmaxf(m, __shfl_xor_sync(0xffffffffu, m, 4));
        m = fmaxf(m, __shfl_xor_sync(0xffffffffu, m, 8));
        m = fmaxf(m, __shfl_xor_sync(0xffffffffu, m, 16));
        const float mw = m * kLog2e;
        float l = 0.f;
        uint32_t* ps = (uint32_t*)(wscr + h * 256) + (t >> 1) * 32 + (g & 3) * 8 + (g >> 2);
#pragma unroll
        for (int i = 0; i < 4; i++) {
            const float p0 = ex2(fmaf(e0[i], kLog2e, -mw)), p1 = ex2(fmaf(e1[i], kLog2e, -mw));
            l += p0 + p1;
            if (valid) ps[2 * i] = pack_bf16(p0, p1);
        }
        l += __shfl_xor_sync(0xffffffffu, l, 1);
        l += __shfl_xor_sync(0xffffffffu, l, 4);
        l += __shfl_xor_sync(0xffffffffu, l, 8);
        l += __shfl_xor_sync(0xffffffffu, l, 16);
        if (lane == 0 || lane == 2) *((float2*)(smem + kOffML) + n * 2 + (t >> 1)) = make_float2(mw, l);
    }
    __syncwarp();
    if (lane == 0) mbar_arrive(bar_k);

    uint32_t cbase = sbase + kOffC + tid * 4;
    uint32_t csend0, csend1, cbar0, cbar1;
    {
        const uint32_t a = sbase + kOffC + rank * 1024 + (warp * 8 + g) * 16;
        csend0 = mapa(a, 2 * t); csend1 = mapa(a, 2 * t + 1);
        cbar0 = mapa(bar_c, 2 * t); cbar1 = mapa(bar_c, 2 * t + 1);
    }
    uint32_t odst16 = sbase + kOffA + (g >> 1) * 144 + (((t & 1) * 8 + warp) * 2 + (t >> 1)) * 4 + (g & 1) * 2;
    uint32_t osrc = sbase + kOffA + (g & 1) * 576 + t * 144;
    uint32_t wbase = sbase + kOffRing + kWoSlot * kTileBytes + ((lane & 7) + ((lane >> 4) & 1) * 8) * (kWoCols * 2) +
                     ((lane >> 3) & 1) * 16 + warp * 32;
    float* rdst = &sc->r[rank][j][(warp * 16 + g + (t & 1) * 8) * 2];
    const float* rsrc = &sc->r[rank][lane >> 2][j * 16 + (lane & 3) * 4];
    __nv_bfloat16* odst;
    {
        const int pq8 = lane >> 2;
        const int e = (lane & 3) * 4 + (pq8 >= 4 ? 2 : 0) + ((pq8 >> 1) & 1);
        odst = out + (e & 1) * kD + rank * kWoCols + j * 8 + (e >> 1);
    }
    pin(cbase); pin(csend0); pin(csend1); pin(cbar0); pin(cbar1); pin(wbase); pin(odst16); pin(osrc);
    pin(rdst); pin(rsrc); pin(odst);

    float o[4] = {0.f, 0.f, 0.f, 0.f};
    {
        float2 gsc = make_float2(0.f, 0.f);
        const uint32_t pa = sbase + kOffA + (g & 1) * 128 + t * 32;
        const uint32_t va = sbase + kOffRing + (warp >> 2) * 8192 + ((lane & 7) + ((lane >> 4) & 1) * 8) * 128 +
                            ((((warp & 3) * 2 + ((lane >> 3) & 1)) ^ (lane & 7)) * 16);
        int slot = kTiles % kNSlot;
        mbar_wait(bar_k, 0);
        float fl;
        {
            const float mt = ldsf(sbase + kOffML + (lane & 15) * 16 + (lane >> 4) * 8);
            float M = mt;
#pragma unroll
            for (int o = 1; o < 16; o <<= 1) M = fmaxf(M, __shfl_xor_sync(0xffffffffu, M, o));
            fl = ex2(mt - M);
        }
#pragma unroll 1
        for (int tau = 0; tau < kTiles; tau++) {
            const uint32_t pw = pa + (tau & 7) * 1024 + (tau >> 3) * 256;
            const uint4 pA = lds128(pw), pB = lds128(pw + 16);
            const float f0 = __shfl_sync(0xffffffffu, fl, tau), f1 = __shfl_sync(0xffffffffu, fl, 16 + tau);
            if (tau == 12) {
                mbar_wait(bar_stat, 0);
                gsc = *(const float2*)(smem + kOffML + 256);
            }
            const uint32_t addr = va + slot * kTileBytes;
            slot = slot == kNSlot - 1 ? 0 : slot + 1;
            mbar_wait(bar_full + (kTiles + tau) * 8, 0);
            const uint4 v0 = ldsm_x4_trans(addr), v1 = ldsm_x4_trans(addr + 2048);
            const uint4 v2 = ldsm_x4_trans(addr + 4096), v3 = ldsm_x4_trans(addr + 6144);
            float a0[4], a1[4];
            mma_bf16_z(a0, v0.x, v0.y, v0.z, v0.w, pA.x, pA.y);
            mma_bf16_z(a1, v1.x, v1.y, v1.z, v1.w, pA.z, pA.w);
            mma_bf16(a0, v2.x, v2.y, v2.z, v2.w, pB.x, pB.y);
            mma_bf16(a1, v3.x, v3.y, v3.z, v3.w, pB.z, pB.w);
            __syncwarp();
            if (lane == 0 && kTiles + tau < kNumEmpty) mbar_arrive(bar_empty + (kTiles + tau) * 8);
            o[0] = fmaf(f0, a0[0] + a1[0], o[0]);
            o[1] = fmaf(f1, a0[1] + a1[1], o[1]);
            o[2] = fmaf(f0, a0[2] + a1[2], o[2]);
            o[3] = fmaf(f1, a0[3] + a1[3], o[3]);
        }
        const float y0 = o[0] * gsc.x, y1 = o[1] * gsc.y, y2 = o[2] * gsc.x, y3 = o[3] * gsc.y;
        st_async_v4(csend0, y0, y1, y2, y3, cbar0);
        st_async_v4(csend1, y0, y1, y2, y3, cbar1);
    }

    {
        mbar_wait(bar_c, 0);
        {
            float a[8];
#pragma unroll
            for (int r = 0; r < 8; r++) a[r] = ldsf(cbase + r * 1024);
            const uint32_t w = pack_bf16((a[0] + a[1]) + (a[2] + a[3]), (a[4] + a[5]) + (a[6] + a[7]));
            asm volatile("st.shared.u16 [%0], %1;" ::"r"(odst16), "h"((unsigned short)w) : "memory");
            asm volatile("st.shared.u16 [%0], %1;" ::"r"(odst16 + 576), "h"((unsigned short)(w >> 16)) : "memory");
        }
        bar_consumers();
        if (warp < 5) {
            uint4 bq[8];
#pragma unroll
            for (int i = 0; i < 8; i++) bq[i] = lds128(osrc + i * 16);
            float acc0[4] = {0.f, 0.f, 0.f, 0.f}, acc1[4] = {0.f, 0.f, 0.f, 0.f};
#pragma unroll
            for (int pp = 0; pp < 2; pp++) {
                uint4 wa[2][2][2];
#pragma unroll
                for (int q = 0; q < 2; q++) {
                    mbar_wait(bar_full + (2 * pp + q) * 8, 1);
#pragma unroll
                    for (int h = 0; h < 2; h++)
#pragma unroll
                        for (int blk = 0; blk < 2; blk++)
                            wa[q][h][blk] = ldsm_x4_trans(wbase + (2 * pp + q) * (kWoBytes / kNWo) +
                                                          (h * kWoRows + blk * 16) * (kWoCols * 2));
                }
#pragma unroll
                for (int q = 0; q < 2; q++)
#pragma unroll
                    for (int h = 0; h < 2; h++) {
                        const uint4 bb = bq[h * 4 + 2 * pp + q];
                        mma_bf16(acc0, wa[q][h][0].x, wa[q][h][0].y, wa[q][h][0].z, wa[q][h][0].w, bb.x, bb.y);
                        mma_bf16(acc1, wa[q][h][1].x, wa[q][h][1].y, wa[q][h][1].z, wa[q][h][1].w, bb.z, bb.w);
                    }
            }
            if (t == 0 || (t == 1 && warp < 4)) {
                const float v0 = t == 0 ? acc0[0] + acc1[0] : acc0[2] + acc1[2];
                const float v1 = t == 0 ? acc0[1] + acc1[1] : acc0[3] + acc1[3];
                asm volatile("st.relaxed.gpu.global.v2.u32 [%0], {%1,%2};" ::"l"(rdst), "r"(tag_f32(v0, tag)),
                             "r"(tag_f32(v1, tag)) : "memory");
            }
        }
        if (warp == 7 && j < 9) {
            mbar_wait(bar_full + (kNWo - 1) * 8, 1);
            const int pq8 = lane >> 2;
            uint4 w0 = ld_rlx_v4(rsrc), w1 = ld_rlx_v4(rsrc + 8 * 144);
            uint32_t it2 = 0;
            while (true) {
                const bool ok0 = tagged4(w0, tag), ok1 = tagged4(w1, tag);
                if (__all_sync(0xffffffffu, ok0 && ok1)) break;
                if (!ok0) w0 = ld_rlx_v4(rsrc);
                if (!ok1) w1 = ld_rlx_v4(rsrc + 8 * 144);
                if (++it2 > kSpinLimit) SPIN_FAIL();
            }
            const float x0 = untag(w0.x) + untag(w1.x), x1 = untag(w0.y) + untag(w1.y);
            const float x2 = untag(w0.z) + untag(w1.z), x3 = untag(w0.w) + untag(w1.w);
            const bool h2 = pq8 >= 4, h1 = (pq8 & 2) != 0;
            const float y0 = (h2 ? x2 : x0) + __shfl_xor_sync(0xffffffffu, h2 ? x0 : x2, 16);
            const float y1 = (h2 ? x3 : x1) + __shfl_xor_sync(0xffffffffu, h2 ? x1 : x3, 16);
            float z = (h1 ? y1 : y0) + __shfl_xor_sync(0xffffffffu, h1 ? y0 : y1, 8);
            z += __shfl_xor_sync(0xffffffffu, z, 4);
            if ((pq8 & 1) == 0) {
                const unsigned short zb = __bfloat16_as_ushort(__float2bfloat16(z));
                asm volatile("st.global.u16 [%0], %1;" ::"l"(odst), "h"(zb) : "memory");
            }
        }
    }
}

}

typedef CUresult (*EncodeTiledFn)(CUtensorMap*, CUtensorMapDataType, cuuint32_t, void*, const cuuint64_t*,
                                  const cuuint64_t*, const cuuint32_t*, const cuuint32_t*, CUtensorMapInterleave,
                                  CUtensorMapSwizzle, CUtensorMapL2promotion, CUtensorMapFloatOOBfill);

extern "C" void kernel_launch(void* const* d_in, const int* in_sizes, int n_in, void* d_out, int out_size) {
    (void)in_sizes; (void)n_in; (void)out_size;
    static EncodeTiledFn encode = nullptr;
    if (!encode) {
        void* fn = nullptr;
        cudaDriverEntryPointQueryResult st;
        cudaGetDriverEntryPoint("cuTensorMapEncodeTiled", &fn, cudaEnableDefault, &st);
        encode = (EncodeTiledFn)fn;
        cudaFuncSetAttribute(decode_attn_kernel, cudaFuncAttributeMaxDynamicSharedMemorySize, kSmemBytes);
    }
    CUtensorMap wq_map, v_map, wo_map;
    const cuuint32_t estr[3] = {1, 1, 1};
    {
        const cuuint64_t dims[2] = {4096, (cuuint64_t)kD};
        const cuuint64_t strides[1] = {4096 * 2};
        const cuuint32_t box[2] = {64, 144};
        encode(&wq_map, CU_TENSOR_MAP_DATA_TYPE_BFLOAT16, 2, d_in[3], dims, strides, box, estr,
               CU_TENSOR_MAP_INTERLEAVE_NONE, CU_TENSOR_MAP_SWIZZLE_128B, CU_TENSOR_MAP_L2_PROMOTION_L2_128B,
               CU_TENSOR_MAP_FLOAT_OOB_FILL_NONE);
    }
    {
        const cuuint64_t dims[3] = {64, (cuuint64_t)2 * 16 * kSK, 2};
        const cuuint64_t strides[2] = {kDH * 2, 128};
        const cuuint32_t box[3] = {64, 64, 2};
        encode(&v_map, CU_TENSOR_MAP_DATA_TYPE_BFLOAT16, 3, d_in[2], dims, strides, box, estr,
               CU_TENSOR_MAP_INTERLEAVE_NONE, CU_TENSOR_MAP_SWIZZLE_128B, CU_TENSOR_MAP_L2_PROMOTION_L2_256B,
               CU_TENSOR_MAP_FLOAT_OOB_FILL_NONE);
    }
    {
        const cuuint64_t dims[3] = {(cuuint64_t)kD, 128, 32};
        const cuuint64_t strides[2] = {(cuuint64_t)kD * 2, (cuuint64_t)kD * 2 * 128};
        const cuuint32_t box[3] = {(cuuint32_t)kWoCols, (cuuint32_t)kWoRows, 2};
        encode(&wo_map, CU_TENSOR_MAP_DATA_TYPE_BFLOAT16, 3, d_in[4], dims, strides, box, estr,
               CU_TENSOR_MAP_INTERLEAVE_NONE, CU_TENSOR_MAP_SWIZZLE_NONE, CU_TENSOR_MAP_L2_PROMOTION_L2_256B,
               CU_TENSOR_MAP_FLOAT_OOB_FILL_NONE);
    }
    decode_attn_kernel<<<kNCTA, kThreads, kSmemBytes, cudaStreamPerThread>>>(
        (const __nv_bfloat16*)d_in[0], (const __nv_bfloat16*)d_in[1], (__nv_bfloat16*)d_out, wq_map, v_map, wo_map);
}
```

```cpp
#include <cuda_runtime.h>
#include <cuda.h>
#include <cuda_bf16.h>
#include <stdint.h>

namespace {

constexpr int kD = 576, kSK = 32768, kDH = 128, kW = 4096;
constexpr int kNCTA = 128;
constexpr int kConsumerWarps = 8;
constexpr int kThreads = 320;
constexpr int kTileBytes = 16384;
constexpr int kNSlot = 6;
constexpr int kInflight = 4;
constexpr int kStart = 3;
constexpr int kWin0 = 3;
constexpr int kBalBias = 120;
constexpr int kBalRate = 112;
constexpr int kBalBehind1 = 64, kBalBehind2 = 192, kBalAhead = 128;
constexpr int kTiles = 16;
constexpr int kNWo = 4;
constexpr int kWoRows = 128 / kNWo;
constexpr int kWoCols = 72;
constexpr int kWoBytes = 256 * kWoCols * 2;
constexpr int kWoSlot = 2;
constexpr int kItems = 2 * kTiles + kNWo;

constexpr int kOffRing = 0;
constexpr int kOffA = kOffRing + kNSlot * kTileBytes;
constexpr int kOffC = kOffA + 8192;
constexpr int kOffQin = kOffC;
constexpr int kOffX = kOffC + 2048;
constexpr int kOffQ = kOffC + 3328;
constexpr int kOffML = kOffC + 8192;
constexpr int kOffMon = kOffML + 256 + 16 + 128;
constexpr int kNumEmpty = 29;
constexpr int kNumFull = 2 * kTiles;
constexpr int kNumBars = kNumFull + kNumEmpty + 8;
constexpr int kWqSlot = 3;
constexpr int kOffBar = kOffMon + 16;
constexpr int kSmemBytes = kOffBar + kNumBars * 8;

constexpr float kScale = 0.08838834764831845f;
constexpr float kLog2e = 1.4426950408889634f;
constexpr uint32_t kSpinLimit = 1u << 22;

struct __align__(128) Scratch {
    unsigned landed;
    unsigned pad[31];
    unsigned cleared;
};
__device__ Scratch g_scratch;

static_assert(kSmemBytes <= 115712, "two CTAs per SM");

#define SPIN_FAIL() __trap()

__device__ __forceinline__ uint32_t smem_u32(const void* p) { return (uint32_t)__cvta_generic_to_shared(p); }
__device__ __forceinline__ void mbar_init(uint32_t bar, uint32_t cnt) {
    asm volatile("mbarrier.init.shared::cta.b64 [%0], %1;" ::"r"(bar), "r"(cnt) : "memory");
}
__device__ __forceinline__ void mbar_expect_tx(uint32_t bar, uint32_t bytes) {
    asm volatile("mbarrier.arrive.expect_tx.shared::cta.b64 _, [%0], %1;" ::"r"(bar), "r"(bytes) : "memory");
}
__device__ __forceinline__ void mbar_arrive(uint32_t bar) {
    asm volatile("mbarrier.arrive.shared::cta.b64 _, [%0];" ::"r"(bar) : "memory");
}
__device__ __forceinline__ bool mbar_try(uint32_t bar, uint32_t parity) {
    uint32_t done;
    asm volatile(
        "{\n.reg .pred p;\n"
        "mbarrier.try_wait.parity.shared::cta.b64 p, [%1], %2;\n"
        "selp.u32 %0, 1, 0, p;\n}"
        : "=r"(done) : "r"(bar), "r"(parity) : "memory");
    return done != 0;
}
__device__ __forceinline__ void mbar_wait(uint32_t bar, uint32_t parity) {
    uint32_t it = 0;
    while (!mbar_try(bar, parity))
        if (++it > kSpinLimit) SPIN_FAIL();
}
__device__ __forceinline__ bool mbar_test(uint32_t bar, uint32_t parity) {
    uint32_t done;
    asm volatile(
        "{\n.reg .pred p;\n"
        "mbarrier.test_wait.parity.shared::cta.b64 p, [%1], %2;\n"
        "selp.u32 %0, 1, 0, p;\n}"
        : "=r"(done) : "r"(bar), "r"(parity) : "memory");
    return done != 0;
}
__device__ __forceinline__ uint32_t clock32() {
    uint32_t c;
    asm volatile("mov.u32 %0, %clock;" : "=r"(c));
    return c;
}
__device__ __forceinline__ uint32_t mapa(uint32_t addr, uint32_t rank) {
    uint32_t r;
    asm("mapa.shared::cluster.u32 %0, %1, %2;" : "=r"(r) : "r"(addr), "r"(rank));
    return r;
}
__device__ __forceinline__ void st_async_u32(uint32_t raddr, uint32_t v, uint32_t rbar) {
    asm volatile("st.async.weak.shared::cluster.mbarrier::complete_tx::bytes.u32 [%0], %1, [%2];"
                 ::"r"(raddr), "r"(v), "r"(rbar) : "memory");
}
__device__ __forceinline__ void st_async_u64(uint32_t raddr, uint64_t v, uint32_t rbar) {
    asm volatile("st.async.weak.shared::cluster.mbarrier::complete_tx::bytes.u64 [%0], %1, [%2];"
                 ::"r"(raddr), "l"(v), "r"(rbar) : "memory");
}
__device__ __forceinline__ void cluster_arrive() { asm volatile("barrier.cluster.arrive.relaxed.aligned;" ::: "memory"); }
__device__ __forceinline__ void cluster_wait() { asm volatile("barrier.cluster.wait.acquire.aligned;" ::: "memory"); }
__device__ __forceinline__ void bulk_g2s(uint32_t dst, const void* src, uint32_t bytes, uint32_t bar, uint64_t pol) {
    asm volatile(
        "cp.async.bulk.shared::cluster.global.mbarrier::complete_tx::bytes.L2::cache_hint [%0], [%1], %2, [%3], %4;"
        ::"r"(dst), "l"(src), "r"(bytes), "r"(bar), "l"(pol) : "memory");
}
__device__ __forceinline__ void tma_3d(uint32_t dst, const CUtensorMap* map, int c0, int c1, int c2, uint32_t bar, uint64_t pol) {
    asm volatile(
        "cp.async.bulk.tensor.3d.shared::cluster.global.mbarrier::complete_tx::bytes.L2::cache_hint"
        " [%0], [%1, {%3, %4, %5}], [%2], %6;"
        ::"r"(dst), "l"(map), "r"(bar), "r"(c0), "r"(c1), "r"(c2), "l"(pol) : "memory");
}
__device__ __forceinline__ void tma_2d(uint32_t dst, const CUtensorMap* map, int c0, int c1, uint32_t bar, uint64_t pol) {
    asm volatile(
        "cp.async.bulk.tensor.2d.shared::cluster.global.mbarrier::complete_tx::bytes.L2::cache_hint"
        " [%0], [%1, {%3, %4}], [%2], %5;"
        ::"r"(dst), "l"(map), "r"(bar), "r"(c0), "r"(c1), "l"(pol) : "memory");
}
__device__ __forceinline__ void st_async_v4(uint32_t raddr, float a, float b, float c, float d, uint32_t rbar) {
    asm volatile("st.async.weak.shared::cluster.mbarrier::complete_tx::bytes.v4.f32 [%0], {%1,%2,%3,%4}, [%5];"
                 ::"r"(raddr), "f"(a), "f"(b), "f"(c), "f"(d), "r"(rbar) : "memory");
}
__device__ __forceinline__ uint4 ldsm_x4_trans(uint32_t addr) {
    uint4 v;
    asm volatile("ldmatrix.sync.aligned.m8n8.x4.trans.shared.b16 {%0,%1,%2,%3}, [%4];"
                 : "=r"(v.x), "=r"(v.y), "=r"(v.z), "=r"(v.w) : "r"(addr) : "memory");
    return v;
}
__device__ __forceinline__ uint4 lds128(uint32_t addr) {
    uint4 v;
    asm volatile("ld.shared.v4.u32 {%0,%1,%2,%3}, [%4];" : "=r"(v.x), "=r"(v.y), "=r"(v.z), "=r"(v.w) : "r"(addr));
    return v;
}
__device__ __forceinline__ float ldsf(uint32_t addr) {
    float v;
    asm volatile("ld.shared.f32 %0, [%1];" : "=f"(v) : "r"(addr));
    return v;
}
__device__ __forceinline__ void pin(uint32_t& v) { asm volatile("" : "+r"(v)); }
template <class T> __device__ __forceinline__ void pin(T*& p) { asm volatile("" : "+l"(p)); }
__device__ __forceinline__ void mma_bf16(float (&c)[4], uint32_t a0, uint32_t a1, uint32_t a2, uint32_t a3,
                                         uint32_t b0, uint32_t b1) {
    asm volatile(
        "mma.sync.aligned.m16n8k16.row.col.f32.bf16.bf16.f32 {%0,%1,%2,%3}, {%4,%5,%6,%7}, {%8,%9}, {%0,%1,%2,%3};"
        : "+f"(c[0]), "+f"(c[1]), "+f"(c[2]), "+f"(c[3])
        : "r"(a0), "r"(a1), "r"(a2), "r"(a3), "r"(b0), "r"(b1));
}
__device__ __forceinline__ void mma_bf16_z(float (&c)[4], uint32_t a0, uint32_t a1, uint32_t a2, uint32_t a3,
                                           uint32_t b0, uint32_t b1) {
    asm volatile(
        "mma.sync.aligned.m16n8k16.row.col.f32.bf16.bf16.f32 {%0,%1,%2,%3}, {%4,%5,%6,%7}, {%8,%9}, {%10,%10,%10,%10};"
        : "=f"(c[0]), "=f"(c[1]), "=f"(c[2]), "=f"(c[3])
        : "r"(a0), "r"(a1), "r"(a2), "r"(a3), "r"(b0), "r"(b1), "f"(0.f));
}
__device__ __forceinline__ uint32_t ld_rlx_u32(const void* p) {
    uint32_t v;
    asm volatile("ld.relaxed.gpu.global.u32 %0, [%1];" : "=r"(v) : "l"(p) : "memory");
    return v;
}
__device__ __forceinline__ uint4 ldg_stream128(const void* p) {
    uint4 v;
    asm volatile("ld.global.nc.L1::no_allocate.v4.u32 {%0,%1,%2,%3}, [%4];"
                 : "=r"(v.x), "=r"(v.y), "=r"(v.z), "=r"(v.w) : "l"(p));
    return v;
}
__device__ __forceinline__ void bar_consumers() { asm volatile("bar.sync 1, 256;" ::: "memory"); }
__device__ __forceinline__ uint32_t pack_bf16(float lo, float hi) {
    uint32_t r;
    asm("cvt.rn.bf16x2.f32 %0, %1, %2;" : "=r"(r) : "f"(hi), "f"(lo));
    return r;
}
__device__ __forceinline__ float ex2(float x) {
    float y;
    asm("ex2.approx.ftz.f32 %0, %1;" : "=f"(y) : "f"(x));
    return y;
}

__global__ void __cluster_dims__(8, 1, 1) __launch_bounds__(kThreads, 2)
decode_attn_kernel(const __nv_bfloat16* __restrict__ x, const __nv_bfloat16* __restrict__ kc,
                   __nv_bfloat16* __restrict__ out, const __grid_constant__ CUtensorMap wq_map,
                   const __grid_constant__ CUtensorMap v_map, const __grid_constant__ CUtensorMap wo_map) {
    extern __shared__ __align__(1024) unsigned char smem[];
    int tid, cta;
    asm volatile("mov.u32 %0, %tid.x;" : "=r"(tid));
    asm volatile("mov.u32 %0, %ctaid.x;" : "=r"(cta));
    const int lane = tid & 31;
    const int warp = __shfl_sync(0xffffffffu, tid >> 5, 0);
    const int j = cta >> 3, rank = cta & 7;
    const int b = rank >> 2, split = rank & 3;
    const int pair = b * 16 + j;
    const int g = lane >> 2, t = lane & 3;
    const uint32_t sbase = smem_u32(smem);
    const uint32_t bar_full = sbase + kOffBar, bar_empty = bar_full + kNumFull * 8;
    const uint32_t bar_q = bar_empty + kNumEmpty * 8, bar_stat = bar_q + 8;
    const uint32_t bar_qin = bar_stat + 8, bar_ml = bar_qin + 8, bar_c = bar_ml + 8;
    const uint32_t bar_wq = bar_c + 8, bar_wqf = bar_wq + 8, bar_k = bar_wqf + 8;
    Scratch* sc = &g_scratch;
    if (warp == kConsumerWarps) {
        const char* kbase = (const char*)kc + ((size_t)pair * kSK + (kSK - kW) + split * 64) * (kDH * 2);
        uint64_t pol;
        asm volatile("createpolicy.fractional.L2::evict_first.b64 %0, 1.0;" : "=l"(pol));
        if (lane == 0) {
            asm volatile("prefetch.tensormap [%0];" ::"l"(&wq_map) : "memory");
            if (sbase & 1023u) __trap();
#pragma unroll
            for (int n = 0; n < kStart; n++) mbar_init(bar_full + n * 8, 1);
            mbar_init(bar_wq, 1);
            asm volatile("fence.mbarrier_init.release.cluster;" ::: "memory");
            mbar_expect_tx(bar_wq, 288 * 128);
#pragma unroll
            for (int h = 0; h < 2; h++)
                tma_2d(sbase + kOffRing + kWqSlot * kTileBytes + h * (144 * 128), &wq_map, j * 256 + (rank & 3) * 64,
                       (rank >> 2) * 288 + h * 144, bar_wq, pol);
#pragma unroll
            for (int n = 0; n < kStart; n++) {
                mbar_expect_tx(bar_full + n * 8, kTileBytes);
                bulk_g2s(sbase + kOffRing + n * kTileBytes, kbase + (size_t)n * (4 * kTileBytes), kTileBytes,
                         bar_full + n * 8, pol);
            }
#pragma unroll 1
            for (int n = kStart; n < kNumBars - 3; n++)
                mbar_init(bar_full + n * 8, n >= kNumFull + kTiles && n < kNumFull + kNumEmpty ? kConsumerWarps : 1);
            mbar_init(bar_wqf, kConsumerWarps);
            mbar_init(bar_k, kConsumerWarps);
            mbar_expect_tx(bar_qin, 2048);
            mbar_expect_tx(bar_ml, 128);
            mbar_expect_tx(bar_c, 8192);
            asm volatile("fence.mbarrier_init.release.cluster;" ::: "memory");
            asm volatile("prefetch.tensormap [%0];" ::"l"(&v_map) : "memory");
            asm volatile("prefetch.tensormap [%0];" ::"l"(&wo_map) : "memory");
            *(volatile uint32_t*)(smem + kOffMon) = 0xFFFFFFFFu;
            *(volatile uint32_t*)(smem + kOffMon + 8) = 0u;
        }
        __syncwarp();
        cluster_arrive();
        asm volatile("bar.arrive 2, 320;" ::: "memory");
        if (lane == 0) {
            const int vrow = pair * kSK + (kSK - kW) + split * 64 - kTiles * 256;
            int next = kStart;
            bool q_ready = false;
            int reported = 0;
#pragma unroll 1
            for (int m = 0; next < kItems; m++) {
                mbar_wait(bar_full + m * 8, 0);
                if (!q_ready) q_ready = mbar_test(bar_q, 0);
                int win = q_ready ? kInflight : kWin0;
                if (m < 2 * kTiles - 1) {
                    asm volatile("red.relaxed.gpu.global.add.u32 [%0], 1;" ::"l"(&sc->landed) : "memory");
                    reported = m + 1;
                }
                if (q_ready) {
                    const unsigned long long gt = *(volatile unsigned long long*)(smem + kOffMon);
                    const uint32_t gl = (uint32_t)gt;
                    const int age = (int)(clock32() - (uint32_t)(gt >> 32));
                    const int lag = (int)gl + ((age * kBalRate) >> 10) + kBalBias - (m + 1) * 128;
                    if (gl != 0xFFFFFFFFu) win += (lag > kBalBehind2) ? 2 : (lag > kBalBehind1) ? 1 : (lag < -kBalAhead) ? -1 : 0;
                }
#pragma unroll 1
                while (next < kItems && ((next < 2 * kTiles ? next : 2 * kTiles + 1 + (next - 2 * kTiles) / 2) <= m + win ||
                                         m >= 2 * kTiles - 1)) {
                    const int n = next++;
                    const uint32_t bar = bar_full + n * 8;
                    if (n < 2 * kTiles) {
                        if (n >= kNSlot) mbar_wait(bar_empty + (n - kNSlot) * 8, 0);
                        else mbar_wait(bar_wqf, 0);
                        mbar_expect_tx(bar, kTileBytes);
                        const uint32_t dst = sbase + kOffRing + (n % kNSlot) * kTileBytes;
                        if (n < kTiles) bulk_g2s(dst, kbase + (size_t)n * (4 * kTileBytes), kTileBytes, bar, pol);
                        else tma_3d(dst, &v_map, 0, vrow + n * 256, 0, bar, pol);
                    } else {
                        const int part = n - 2 * kTiles;
                        mbar_wait(bar_empty + (26 + (part * (kWoBytes / kNWo)) / kTileBytes) * 8, 0);
                        mbar_wait(bar_empty + (26 + ((part + 1) * (kWoBytes / kNWo) - 1) / kTileBytes) * 8, 0);
                        mbar_expect_tx(bar_full + part * 8, kWoBytes / kNWo);
                        tma_3d(sbase + kOffRing + kWoSlot * kTileBytes + part * (kWoBytes / kNWo), &wo_map, rank * kWoCols,
                               part * kWoRows, 2 * j, bar_full + part * 8, pol);
                    }
                }
            }
            *(volatile uint32_t*)(smem + kOffMon + 8) = 1u;
            asm volatile("red.relaxed.gpu.global.add.u32 [%0], %1;" ::"l"(&sc->landed), "r"(2 * kTiles - reported) : "memory");
        }
        return;
    }
    cluster_arrive();
    if (warp == kConsumerWarps + 1) {
        const uint32_t epoch = ld_rlx_u32(&sc->landed) >> 12;
        if (cta == 0) {
#pragma unroll
            for (int i = 0; i < 2 * kD / 64; i++)
                asm volatile("st.relaxed.gpu.global.u32 [%0], %1;" ::"l"((uint32_t*)out + i * 32 + lane), "r"(0u) : "memory");
            __syncwarp();
        }
        asm volatile("bar.sync 2, 320;" ::: "memory");
        cluster_wait();
        const uint32_t base = epoch * 4096u;
        if (cta == 0 && lane == 0)
            asm volatile("st.release.gpu.global.u32 [%0], %1;" ::"l"(&sc->cleared), "r"(epoch + 1u) : "memory");
        bool cleared = false;
        const int hd = lane >> 4;
        int state = 0;
        float Mc = 0.f;
        uint32_t it = 0;
        while (true) {
            if (lane == 0) {
                const uint32_t c0 = clock32();
                const uint32_t gl = ld_rlx_u32(&sc->landed) - base;
                uint32_t c1;
                asm volatile("{ .reg .u32 d; and.b32 d, %1, 0; mov.u32 %0, %clock; add.u32 %0, %0, d; }" : "=r"(c1) : "r"(gl) : "memory");
                *(volatile unsigned long long*)(smem + kOffMon) = ((unsigned long long)(c0 + ((c1 - c0) >> 1)) << 32) | gl;
            }
            if (state == 0 && __all_sync(0xffffffffu, mbar_test(bar_k, 0))) {
                const float2 v = *((const float2*)(smem + kOffML) + (lane & 15) * 2 + hd);
                float M = v.x;
#pragma unroll
                for (int o = 1; o < 16; o <<= 1) M = fmaxf(M, __shfl_xor_sync(0xffffffffu, M, o));
                float L = v.y * ex2(v.x - M);
#pragma unroll
                for (int o = 1; o < 16; o <<= 1) L += __shfl_xor_sync(0xffffffffu, L, o);
                Mc = M;
                if ((lane & 15) < 8)
                    st_async_u64(mapa(sbase + kOffML + 272 + (rank * 2 + hd) * 8, lane & 7),
                                 ((uint64_t)__float_as_uint(L) << 32) | __float_as_uint(M), mapa(bar_ml, lane & 7));
                state = 1;
            }
            if (!cleared) {
                uint32_t f = 0;
                if (lane == 0) asm volatile("ld.acquire.gpu.global.u32 %0, [%1];" : "=r"(f) : "l"(&sc->cleared) : "memory");
                cleared = __shfl_sync(0xffffffffu, f, 0) == epoch + 1u;
            }
            if (state == 1 && cleared && __all_sync(0xffffffffu, mbar_test(bar_ml, 0))) {
                const uint64_t w = *(const uint64_t*)(smem + kOffML + 272 + ((b * 4 + (lane & 3)) * 2 + hd) * 8);
                const float Mi = __uint_as_float((uint32_t)w), Li = __uint_as_float((uint32_t)(w >> 32));
                float Mg = fmaxf(Mi, __shfl_xor_sync(0xffffffffu, Mi, 1));
                Mg = fmaxf(Mg, __shfl_xor_sync(0xffffffffu, Mg, 2));
                float Lg = Li * ex2(Mi - Mg);
                Lg += __shfl_xor_sync(0xffffffffu, Lg, 1);
                Lg += __shfl_xor_sync(0xffffffffu, Lg, 2);
                if ((lane & 15) == 0) *((float*)(smem + kOffML + 256) + hd) = ex2(Mc - Mg) / Lg;
                __syncwarp();
                if (lane == 0) mbar_arrive(bar_stat);
                state = 2;
            }
            if (state == 2 && __any_sync(0xffffffffu, *(volatile uint32_t*)(smem + kOffMon + 8) != 0u)) break;
            if (++it > kSpinLimit) SPIN_FAIL();
        }
        return;
    }
    unsigned char* const wscr = smem + kOffA + warp * 1024;
    {
        uint4 wv[9];
        uint32_t xb[9];
        if (tid < 72) {
            const int bb = tid >= 36 ? 1 : 0;
            *(uint4*)(smem + kOffX + tid * 16) =
                ldg_stream128((const uint4*)(x + bb * kD + (rank >> 2) * 288) + (tid - bb * 36));
        }
        asm volatile("bar.sync 2, 320;" ::: "memory");
        {
            const unsigned short* xs = (const unsigned short*)(smem + kOffX) + ((g >> 1) & 1) * 288 + warp * 36;
#pragma unroll
            for (int i = 0; i < 8; i++) xb[i] = xs[2 * t + (i & 1) + 8 * (i >> 1)];
            xb[8] = xs[32 + t];
        }
        mbar_wait(bar_wq, 0);
#pragma unroll
        for (int i = 0; i < 9; i++) {
            const int r = warp * 36 + (i < 8 ? 2 * t + (i & 1) + 8 * (i >> 1) : 32 + t);
            wv[i] = lds128(sbase + kOffRing + kWqSlot * kTileBytes + r * 128 + ((g ^ (r & 7)) * 16));
        }
        float qa[4], qb[4];
        const int sh = (g & 1) * 16;
#pragma unroll
        for (int i = 0; i < 9; i++) xb[i] <<= sh;
        mma_bf16_z(qa, wv[0].x, wv[0].z, wv[1].x, wv[1].z, xb[0], xb[1]);
        mma_bf16_z(qb, wv[0].y, wv[0].w, wv[1].y, wv[1].w, xb[0], xb[1]);
#pragma unroll
        for (int u = 1; u < 4; u++) {
            mma_bf16(qa, wv[2 * u].x, wv[2 * u].z, wv[2 * u + 1].x, wv[2 * u + 1].z, xb[2 * u], xb[2 * u + 1]);
            mma_bf16(qb, wv[2 * u].y, wv[2 * u].w, wv[2 * u + 1].y, wv[2 * u + 1].w, xb[2 * u], xb[2 * u + 1]);
        }
        mma_bf16(qa, wv[8].x, wv[8].z, 0u, 0u, xb[8], 0u);
        mma_bf16(qb, wv[8].y, wv[8].w, 0u, 0u, xb[8], 0u);
        __syncwarp();
        if (lane == 0) mbar_arrive(bar_wqf);
        if (t < 2) {
            float4* dst = (float4*)(wscr + 512 + t * 256 + g * 32);
            dst[0] = make_float4(qa[0], qa[1], qb[0], qb[1]);
            dst[1] = make_float4(qa[2], qa[3], qb[2], qb[3]);
        }
        bar_consumers();
        cluster_wait();
        if (tid < 128) {
            const float* pp = (const float*)(smem + kOffA + 512) + tid;
            float s0 = 0.f;
#pragma unroll
            for (int w = 0; w < 8; w++) s0 += pp[w * 256];
            const uint32_t dst = sbase + kOffQin + ((rank >> 2) * 256 + (rank & 3) * 64 + (tid & 63)) * 4;
            const int r0 = (tid >> 6) * 4;
#pragma unroll
            for (int s = 0; s < 4; s++) st_async_u32(mapa(dst, r0 + s), __float_as_uint(s0), mapa(bar_qin, r0 + s));
        }
        mbar_wait(bar_qin, 0);
        {
            const float* qi = (const float*)(smem + kOffQin) + tid;
            ((__nv_bfloat16*)(smem + kOffQ))[tid] = __float2bfloat16(qi[0] + qi[256]);
        }
        bar_consumers();
        if (tid == 0) mbar_arrive(bar_q);
    }
    uint4 qf[4];
#pragma unroll
    for (int i = 0; i < 4; i++)
        qf[i] = lds128(sbase + kOffQ + (g & 1) * 256 + (4 * (i ^ ((g >> 1) & 1)) + t) * 16);

#pragma unroll 1
    for (int h = 0; h < 2; h++) {
        const int n = warp + 8 * h;
        mbar_wait(bar_full + n * 8, 0);
        const uint32_t kb = sbase + kOffRing + (n % kNSlot) * kTileBytes + g * 512 + t * 16;
        float s[4][4];
#pragma unroll
        for (int mt = 0; mt < 4; mt++) {
#pragma unroll
            for (int i = 0; i < 4; i++) {
                const uint32_t addr = kb + mt * 4096 + ((i ^ (g & 1)) * 64);
                const uint4 ra = lds128(addr), rb = lds128(addr + 256);
                if (i == 0) mma_bf16_z(s[mt], ra.x, rb.x, ra.y, rb.y, qf[i].x, qf[i].y);
                else mma_bf16(s[mt], ra.x, rb.x, ra.y, rb.y, qf[i].x, qf[i].y);
                mma_bf16(s[mt], ra.z, rb.z, ra.w, rb.w, qf[i].z, qf[i].w);
            }
        }
        __syncwarp();
        if (lane == 0) mbar_arrive(bar_empty + n * 8);
        const bool valid = ((t ^ g) & 1) == 0;
        const bool hi = t >= 2;
        float e0[4], e1[4];
        float m = -INFINITY;
#pragma unroll
        for (int i = 0; i < 4; i++) {
            e0[i] = valid ? (hi ? s[i][1] : s[i][0]) : -INFINITY;
            e1[i] = valid ? (hi ? s[i][3] : s[i][2]) : -INFINITY;
            uint32_t r = pack_bf16(e0[i], e1[i]);
            r = pack_bf16(__uint_as_float(r << 16) * kScale, __uint_as_float(r & 0xFFFF0000u) * kScale);
            e0[i] = __uint_as_float(r << 16);
            e1[i] = __uint_as_float(r & 0xFFFF0000u);
            m = fmaxf(m, fmaxf(e0[i], e1[i]));
        }
        m = fmaxf(m, __shfl_xor_sync(0xffffffffu, m, 1));
        m = fmaxf(m, __shfl_xor_sync(0xffffffffu, m, 4));
        m = fmaxf(m, __shfl_xor_sync(0xffffffffu, m, 8));
        m = fmaxf(m, __shfl_xor_sync(0xffffffffu, m, 16));
        const float mw = m * kLog2e;
        float l = 0.f;
        uint32_t* ps = (uint32_t*)(wscr + h * 256) + (t >> 1) * 32 + (g & 3) * 8 + (g >> 2);
#pragma unroll
        for (int i = 0; i < 4; i++) {
            const float p0 = ex2(fmaf(e0[i], kLog2e, -mw)), p1 = ex2(fmaf(e1[i], kLog2e, -mw));
            l += p0 + p1;
            if (valid) ps[2 * i] = pack_bf16(p0, p1);
        }
        l += __shfl_xor_sync(0xffffffffu, l, 1);
        l += __shfl_xor_sync(0xffffffffu, l, 4);
        l += __shfl_xor_sync(0xffffffffu, l, 8);
        l += __shfl_xor_sync(0xffffffffu, l, 16);
        if (lane == 0 || lane == 2) *((float2*)(smem + kOffML) + n * 2 + (t >> 1)) = make_float2(mw, l);
    }
    __syncwarp();
    if (lane == 0) mbar_arrive(bar_k);

    uint32_t cbase = sbase + kOffC + tid * 4;
    uint32_t csend0, csend1, cbar0, cbar1;
    {
        const uint32_t a = sbase + kOffC + rank * 1024 + (warp * 8 + g) * 16;
        csend0 = mapa(a, 2 * t); csend1 = mapa(a, 2 * t + 1);
        cbar0 = mapa(bar_c, 2 * t); cbar1 = mapa(bar_c, 2 * t + 1);
    }
    uint32_t odst16 = sbase + kOffA + (g >> 1) * 144 + (((t & 1) * 8 + warp) * 2 + (t >> 1)) * 4 + (g & 1) * 2;
    uint32_t osrc = sbase + kOffA + (g & 1) * 576 + t * 144;
    uint32_t wbase = sbase + kOffRing + kWoSlot * kTileBytes + ((lane & 7) + ((lane >> 4) & 1) * 8) * (kWoCols * 2) +
                     ((lane >> 3) & 1) * 16 + warp * 32;
    uint32_t* odst = (uint32_t*)(out + (t & 1) * kD + rank * kWoCols + warp * 16 + (t >> 1) * 8) + (g >> 1);
    pin(cbase); pin(csend0); pin(csend1); pin(cbar0); pin(cbar1); pin(wbase); pin(odst16); pin(osrc);
    pin(odst);

    float o[4] = {0.f, 0.f, 0.f, 0.f};
    {
        float2 gsc = make_float2(0.f, 0.f);
        const uint32_t pa = sbase + kOffA + (g & 1) * 128 + t * 32;
        const uint32_t va = sbase + kOffRing + (warp >> 2) * 8192 + ((lane & 7) + ((lane >> 4) & 1) * 8) * 128 +
                            ((((warp & 3) * 2 + ((lane >> 3) & 1)) ^ (lane & 7)) * 16);
        int slot = kTiles % kNSlot;
        mbar_wait(bar_k, 0);
        float fl;
        {
            const float mt = ldsf(sbase + kOffML + (lane & 15) * 16 + (lane >> 4) * 8);
            float M = mt;
#pragma unroll
            for (int o = 1; o < 16; o <<= 1) M = fmaxf(M, __shfl_xor_sync(0xffffffffu, M, o));
            fl = ex2(mt - M);
        }
#pragma unroll 1
        for (int tau = 0; tau < kTiles; tau++) {
            const uint32_t pw = pa + (tau & 7) * 1024 + (tau >> 3) * 256;
            const uint4 pA = lds128(pw), pB = lds128(pw + 16);
            const float f0 = __shfl_sync(0xffffffffu, fl, tau), f1 = __shfl_sync(0xffffffffu, fl, 16 + tau);
            if (tau == 12) {
                mbar_wait(bar_stat, 0);
                gsc = *(const float2*)(smem + kOffML + 256);
            }
            const uint32_t addr = va + slot * kTileBytes;
            slot = slot == kNSlot - 1 ? 0 : slot + 1;
            mbar_wait(bar_full + (kTiles + tau) * 8, 0);
            const uint4 v0 = ldsm_x4_trans(addr), v1 = ldsm_x4_trans(addr + 2048);
            const uint4 v2 = ldsm_x4_trans(addr + 4096), v3 = ldsm_x4_trans(addr + 6144);
            float a0[4], a1[4];
            mma_bf16_z(a0, v0.x, v0.y, v0.z, v0.w, pA.x, pA.y);
            mma_bf16_z(a1, v1.x, v1.y, v1.z, v1.w, pA.z, pA.w);
            mma_bf16(a0, v2.x, v2.y, v2.z, v2.w, pB.x, pB.y);
            mma_bf16(a1, v3.x, v3.y, v3.z, v3.w, pB.z, pB.w);
            __syncwarp();
            if (lane == 0 && kTiles + tau < kNumEmpty) mbar_arrive(bar_empty + (kTiles + tau) * 8);
            o[0] = fmaf(f0, a0[0] + a1[0], o[0]);
            o[1] = fmaf(f1, a0[1] + a1[1], o[1]);
            o[2] = fmaf(f0, a0[2] + a1[2], o[2]);
            o[3] = fmaf(f1, a0[3] + a1[3], o[3]);
        }
        const float y0 = o[0] * gsc.x, y1 = o[1] * gsc.y, y2 = o[2] * gsc.x, y3 = o[3] * gsc.y;
        st_async_v4(csend0, y0, y1, y2, y3, cbar0);
        st_async_v4(csend1, y0, y1, y2, y3, cbar1);
    }

    {
        mbar_wait(bar_c, 0);
        {
            float a[8];
#pragma unroll
            for (int r = 0; r < 8; r++) a[r] = ldsf(cbase + r * 1024);
            const uint32_t w = pack_bf16((a[0] + a[1]) + (a[2] + a[3]), (a[4] + a[5]) + (a[6] + a[7]));
            asm volatile("st.shared.u16 [%0], %1;" ::"r"(odst16), "h"((unsigned short)w) : "memory");
            asm volatile("st.shared.u16 [%0], %1;" ::"r"(odst16 + 576), "h"((unsigned short)(w >> 16)) : "memory");
        }
        bar_consumers();
        if (warp < 5) {
            uint4 bq[8];
#pragma unroll
            for (int i = 0; i < 8; i++) bq[i] = lds128(osrc + i * 16);
            float acc0[4] = {0.f, 0.f, 0.f, 0.f}, acc1[4] = {0.f, 0.f, 0.f, 0.f};
#pragma unroll
            for (int pp = 0; pp < 2; pp++) {
                uint4 wa[2][2][2];
#pragma unroll
                for (int q = 0; q < 2; q++) {
                    mbar_wait(bar_full + (2 * pp + q) * 8, 1);
#pragma unroll
                    for (int h = 0; h < 2; h++)
#pragma unroll
                        for (int blk = 0; blk < 2; blk++)
                            wa[q][h][blk] = ldsm_x4_trans(wbase + (2 * pp + q) * (kWoBytes / kNWo) +
                                                          (h * kWoRows + blk * 16) * (kWoCols * 2));
                }
#pragma unroll
                for (int q = 0; q < 2; q++)
#pragma unroll
                    for (int h = 0; h < 2; h++) {
                        const uint4 bb = bq[h * 4 + 2 * pp + q];
                        mma_bf16(acc0, wa[q][h][0].x, wa[q][h][0].y, wa[q][h][0].z, wa[q][h][0].w, bb.x, bb.y);
                        mma_bf16(acc1, wa[q][h][1].x, wa[q][h][1].y, wa[q][h][1].z, wa[q][h][1].w, bb.z, bb.w);
                    }
            }
            const float lo = (t & 1) ? acc0[1] + acc1[1] : acc0[0] + acc1[0];
            const float hi = (t & 1) ? acc0[3] + acc1[3] : acc0[2] + acc1[2];
            const float v = (t & 2) ? hi : lo;
            const uint32_t w = (g & 1) ? pack_bf16(-0.f, v) : pack_bf16(v, -0.f);
            if (warp < 4 || t < 2)
                asm volatile("red.relaxed.gpu.global.add.noftz.bf16x2 [%0], %1;" ::"l"(odst), "r"(w) : "memory");
        }
    }
}

}

typedef CUresult (*EncodeTiledFn)(CUtensorMap*, CUtensorMapDataType, cuuint32_t, void*, const cuuint64_t*,
                                  const cuuint64_t*, const cuuint32_t*, const cuuint32_t*, CUtensorMapInterleave,
                                  CUtensorMapSwizzle, CUtensorMapL2promotion, CUtensorMapFloatOOBfill);

extern "C" void kernel_launch(void* const* d_in, const int* in_sizes, int n_in, void* d_out, int out_size) {
    (void)in_sizes; (void)n_in; (void)out_size;
    static EncodeTiledFn encode = nullptr;
    if (!encode) {
        void* fn = nullptr;
        cudaDriverEntryPointQueryResult st;
        cudaGetDriverEntryPoint("cuTensorMapEncodeTiled", &fn, cudaEnableDefault, &st);
        encode = (EncodeTiledFn)fn;
        cudaFuncSetAttribute(decode_attn_kernel, cudaFuncAttributeMaxDynamicSharedMemorySize, kSmemBytes);
    }
    CUtensorMap wq_map, v_map, wo_map;
    const cuuint32_t estr[3] = {1, 1, 1};
    {
        const cuuint64_t dims[2] = {4096, (cuuint64_t)kD};
        const cuuint64_t strides[1] = {4096 * 2};
        const cuuint32_t box[2] = {64, 144};
        encode(&wq_map, CU_TENSOR_MAP_DATA_TYPE_BFLOAT16, 2, d_in[3], dims, strides, box, estr,
               CU_TENSOR_MAP_INTERLEAVE_NONE, CU_TENSOR_MAP_SWIZZLE_128B, CU_TENSOR_MAP_L2_PROMOTION_L2_128B,
               CU_TENSOR_MAP_FLOAT_OOB_FILL_NONE);
    }
    {
        const cuuint64_t dims[3] = {64, (cuuint64_t)2 * 16 * kSK, 2};
        const cuuint64_t strides[2] = {kDH * 2, 128};
        const cuuint32_t box[3] = {64, 64, 2};
        encode(&v_map, CU_TENSOR_MAP_DATA_TYPE_BFLOAT16, 3, d_in[2], dims, strides, box, estr,
               CU_TENSOR_MAP_INTERLEAVE_NONE, CU_TENSOR_MAP_SWIZZLE_128B, CU_TENSOR_MAP_L2_PROMOTION_L2_256B,
               CU_TENSOR_MAP_FLOAT_OOB_FILL_NONE);
    }
    {
        const cuuint64_t dims[3] = {(cuuint64_t)kD, 128, 32};
        const cuuint64_t strides[2] = {(cuuint64_t)kD * 2, (cuuint64_t)kD * 2 * 128};
        const cuuint32_t box[3] = {(cuuint32_t)kWoCols, (cuuint32_t)kWoRows, 2};
        encode(&wo_map, CU_TENSOR_MAP_DATA_TYPE_BFLOAT16, 3, d_in[4], dims, strides, box, estr,
               CU_TENSOR_MAP_INTERLEAVE_NONE, CU_TENSOR_MAP_SWIZZLE_NONE, CU_TENSOR_MAP_L2_PROMOTION_L2_256B,
               CU_TENSOR_MAP_FLOAT_OOB_FILL_NONE);
    }
    decode_attn_kernel<<<kNCTA, kThreads, kSmemBytes, cudaStreamPerThread>>>(
        (const __nv_bfloat16*)d_in[0], (const __nv_bfloat16*)d_in[1], (__nv_bfloat16*)d_out, wq_map, v_map, wo_map);
}
```

```cpp
#include <cuda_runtime.h>
#include <cuda.h>
#include <cuda_bf16.h>
#include <stdint.h>

namespace {

constexpr int kD = 576, kSK = 32768, kDH = 128, kW = 4096;
constexpr int kNCTA = 128;
constexpr int kConsumerWarps = 8;
constexpr int kThreads = 320;
constexpr int kTileBytes = 16384;
constexpr int kNSlot = 6;
constexpr int kInflight = 4;
constexpr int kStart = 3;
constexpr int kWin0 = 3;
constexpr int kBalBias = 120;
constexpr int kBalRate = 112;
constexpr int kBalBehind1 = 64, kBalBehind2 = 192, kBalAhead = 128;
constexpr int kTiles = 16;
constexpr int kNWo = 4;
constexpr int kWoRows = 128 / kNWo;
constexpr int kWoCols = 72;
constexpr int kWoBytes = 256 * kWoCols * 2;
constexpr int kWoSlot = 2;
constexpr int kItems = 2 * kTiles + kNWo;

constexpr int kOffRing = 0;
constexpr int kOffA = kOffRing + kNSlot * kTileBytes;
constexpr int kOffC = kOffA + 8192;
constexpr int kOffQin = kOffC;
constexpr int kOffX = kOffC + 2048;
constexpr int kOffQ = kOffC + 3328;
constexpr int kOffML = kOffC + 8192;
constexpr int kOffMon = kOffML + 256 + 16 + 128;
constexpr int kNumEmpty = 29;
constexpr int kNumFull = 2 * kTiles;
constexpr int kNumBars = kNumFull + kNumEmpty + 8;
constexpr int kWqSlot = 3;
constexpr int kOffBar = kOffMon + 16;
constexpr int kSmemBytes = kOffBar + kNumBars * 8;

constexpr float kScale = 0.08838834764831845f;
constexpr float kLog2e = 1.4426950408889634f;
constexpr uint32_t kSpinLimit = 1u << 22;

struct __align__(128) Scratch {
    unsigned landed;
    unsigned pad[31];
    unsigned cleared;
};
__device__ Scratch g_scratch;

static_assert(kSmemBytes <= 115712, "two CTAs per SM");

#define SPIN_FAIL() __trap()

__device__ __forceinline__ uint32_t smem_u32(const void* p) { return (uint32_t)__cvta_generic_to_shared(p); }
__device__ __forceinline__ void mbar_init(uint32_t bar, uint32_t cnt) {
    asm volatile("mbarrier.init.shared::cta.b64 [%0], %1;" ::"r"(bar), "r"(cnt) : "memory");
}
__device__ __forceinline__ void mbar_expect_tx(uint32_t bar, uint32_t bytes) {
    asm volatile("mbarrier.arrive.expect_tx.shared::cta.b64 _, [%0], %1;" ::"r"(bar), "r"(bytes) : "memory");
}
__device__ __forceinline__ void mbar_arrive(uint32_t bar) {
    asm volatile("mbarrier.arrive.shared::cta.b64 _, [%0];" ::"r"(bar) : "memory");
}
__device__ __forceinline__ bool mbar_try(uint32_t bar, uint32_t parity) {
    uint32_t done;
    asm volatile(
        "{\n.reg .pred p;\n"
        "mbarrier.try_wait.parity.shared::cta.b64 p, [%1], %2;\n"
        "selp.u32 %0, 1, 0, p;\n}"
        : "=r"(done) : "r"(bar), "r"(parity) : "memory");
    return done != 0;
}
__device__ __forceinline__ void mbar_wait(uint32_t bar, uint32_t parity) {
    uint32_t it = 0;
    while (!mbar_try(bar, parity))
        if (++it > kSpinLimit) SPIN_FAIL();
}
__device__ __forceinline__ bool mbar_test(uint32_t bar, uint32_t parity) {
    uint32_t done;
    asm volatile(
        "{\n.reg .pred p;\n"
        "mbarrier.test_wait.parity.shared::cta.b64 p, [%1], %2;\n"
        "selp.u32 %0, 1, 0, p;\n}"
        : "=r"(done) : "r"(bar), "r"(parity) : "memory");
    return done != 0;
}
__device__ __forceinline__ uint32_t clock32() {
    uint32_t c;
    asm volatile("mov.u32 %0, %clock;" : "=r"(c));
    return c;
}
__device__ __forceinline__ uint32_t mapa(uint32_t addr, uint32_t rank) {
    uint32_t r;
    asm("mapa.shared::cluster.u32 %0, %1, %2;" : "=r"(r) : "r"(addr), "r"(rank));
    return r;
}
__device__ __forceinline__ void st_async_u32(uint32_t raddr, uint32_t v, uint32_t rbar) {
    asm volatile("st.async.weak.shared::cluster.mbarrier::complete_tx::bytes.u32 [%0], %1, [%2];"
                 ::"r"(raddr), "r"(v), "r"(rbar) : "memory");
}
__device__ __forceinline__ void st_async_u64(uint32_t raddr, uint64_t v, uint32_t rbar) {
    asm volatile("st.async.weak.shared::cluster.mbarrier::complete_tx::bytes.u64 [%0], %1, [%2];"
                 ::"r"(raddr), "l"(v), "r"(rbar) : "memory");
}
__device__ __forceinline__ void cluster_arrive() { asm volatile("barrier.cluster.arrive.relaxed.aligned;" ::: "memory"); }
__device__ __forceinline__ void cluster_wait() { asm volatile("barrier.cluster.wait.acquire.aligned;" ::: "memory"); }
__device__ __forceinline__ void bulk_g2s(uint32_t dst, const void* src, uint32_t bytes, uint32_t bar, uint64_t pol) {
    asm volatile(
        "cp.async.bulk.shared::cluster.global.mbarrier::complete_tx::bytes.L2::cache_hint [%0], [%1], %2, [%3], %4;"
        ::"r"(dst), "l"(src), "r"(bytes), "r"(bar), "l"(pol) : "memory");
}
__device__ __forceinline__ void tma_3d(uint32_t dst, const CUtensorMap* map, int c0, int c1, int c2, uint32_t bar, uint64_t pol) {
    asm volatile(
        "cp.async.bulk.tensor.3d.shared::cluster.global.mbarrier::complete_tx::bytes.L2::cache_hint"
        " [%0], [%1, {%3, %4, %5}], [%2], %6;"
        ::"r"(dst), "l"(map), "r"(bar), "r"(c0), "r"(c1), "r"(c2), "l"(pol) : "memory");
}
__device__ __forceinline__ void tma_2d(uint32_t dst, const CUtensorMap* map, int c0, int c1, uint32_t bar, uint64_t pol) {
    asm volatile(
        "cp.async.bulk.tensor.2d.shared::cluster.global.mbarrier::complete_tx::bytes.L2::cache_hint"
        " [%0], [%1, {%3, %4}], [%2], %5;"
        ::"r"(dst), "l"(map), "r"(bar), "r"(c0), "r"(c1), "l"(pol) : "memory");
}
__device__ __forceinline__ void st_async_v4(uint32_t raddr, float a, float b, float c, float d, uint32_t rbar) {
    asm volatile("st.async.weak.shared::cluster.mbarrier::complete_tx::bytes.v4.f32 [%0], {%1,%2,%3,%4}, [%5];"
                 ::"r"(raddr), "f"(a), "f"(b), "f"(c), "f"(d), "r"(rbar) : "memory");
}
__device__ __forceinline__ uint4 ldsm_x4_trans(uint32_t addr) {
    uint4 v;
    asm volatile("ldmatrix.sync.aligned.m8n8.x4.trans.shared.b16 {%0,%1,%2,%3}, [%4];"
                 : "=r"(v.x), "=r"(v.y), "=r"(v.z), "=r"(v.w) : "r"(addr) : "memory");
    return v;
}
__device__ __forceinline__ uint4 lds128(uint32_t addr) {
    uint4 v;
    asm volatile("ld.shared.v4.u32 {%0,%1,%2,%3}, [%4];" : "=r"(v.x), "=r"(v.y), "=r"(v.z), "=r"(v.w) : "r"(addr));
    return v;
}
__device__ __forceinline__ float ldsf(uint32_t addr) {
    float v;
    asm volatile("ld.shared.f32 %0, [%1];" : "=f"(v) : "r"(addr));
    return v;
}
__device__ __forceinline__ void pin(uint32_t& v) { asm volatile("" : "+r"(v)); }
template <class T> __device__ __forceinline__ void pin(T*& p) { asm volatile("" : "+l"(p)); }
__device__ __forceinline__ void mma_bf16(float (&c)[4], uint32_t a0, uint32_t a1, uint32_t a2, uint32_t a3,
                                         uint32_t b0, uint32_t b1) {
    asm volatile(
        "mma.sync.aligned.m16n8k16.row.col.f32.bf16.bf16.f32 {%0,%1,%2,%3}, {%4,%5,%6,%7}, {%8,%9}, {%0,%1,%2,%3};"
        : "+f"(c[0]), "+f"(c[1]), "+f"(c[2]), "+f"(c[3])
        : "r"(a0), "r"(a1), "r"(a2), "r"(a3), "r"(b0), "r"(b1));
}
__device__ __forceinline__ void mma_bf16_z(float (&c)[4], uint32_t a0, uint32_t a1, uint32_t a2, uint32_t a3,
                                           uint32_t b0, uint32_t b1) {
    asm volatile(
        "mma.sync.aligned.m16n8k16.row.col.f32.bf16.bf16.f32 {%0,%1,%2,%3}, {%4,%5,%6,%7}, {%8,%9}, {%10,%10,%10,%10};"
        : "=f"(c[0]), "=f"(c[1]), "=f"(c[2]), "=f"(c[3])
        : "r"(a0), "r"(a1), "r"(a2), "r"(a3), "r"(b0), "r"(b1), "f"(0.f));
}
__device__ __forceinline__ uint32_t ld_rlx_u32(const void* p) {
    uint32_t v;
    asm volatile("ld.relaxed.gpu.global.u32 %0, [%1];" : "=r"(v) : "l"(p) : "memory");
    return v;
}
__device__ __forceinline__ uint4 ldg_stream128(const void* p) {
    uint4 v;
    asm volatile("ld.global.nc.L1::no_allocate.v4.u32 {%0,%1,%2,%3}, [%4];"
                 : "=r"(v.x), "=r"(v.y), "=r"(v.z), "=r"(v.w) : "l"(p));
    return v;
}
__device__ __forceinline__ void bar_consumers() { asm volatile("bar.sync 1, 256;" ::: "memory"); }
__device__ __forceinline__ uint32_t pack_bf16(float lo, float hi) {
    uint32_t r;
    asm("cvt.rn.bf16x2.f32 %0, %1, %2;" : "=r"(r) : "f"(hi), "f"(lo));
    return r;
}
__device__ __forceinline__ float ex2(float x) {
    float y;
    asm("ex2.approx.ftz.f32 %0, %1;" : "=f"(y) : "f"(x));
    return y;
}

__global__ void __cluster_dims__(8, 1, 1) __launch_bounds__(kThreads, 2)
decode_attn_kernel(const __nv_bfloat16* __restrict__ x, const __nv_bfloat16* __restrict__ kc,
                   __nv_bfloat16* __restrict__ out, const __grid_constant__ CUtensorMap wq_map,
                   const __grid_constant__ CUtensorMap v_map, const __grid_constant__ CUtensorMap wo_map) {
    extern __shared__ __align__(1024) unsigned char smem[];
    int tid, cta;
    asm volatile("mov.u32 %0, %tid.x;" : "=r"(tid));
    asm volatile("mov.u32 %0, %ctaid.x;" : "=r"(cta));
    const int lane = tid & 31;
    const int warp = __shfl_sync(0xffffffffu, tid >> 5, 0);
    const int j = cta >> 3, rank = cta & 7;
    const int b = rank >> 2, split = rank & 3;
    const int pair = b * 16 + j;
    const int g = lane >> 2, t = lane & 3;
    const uint32_t sbase = smem_u32(smem);
    const uint32_t bar_full = sbase + kOffBar, bar_empty = bar_full + kNumFull * 8;
    const uint32_t bar_q = bar_empty + kNumEmpty * 8, bar_stat = bar_q + 8;
    const uint32_t bar_qin = bar_stat + 8, bar_ml = bar_qin + 8, bar_c = bar_ml + 8;
    const uint32_t bar_wq = bar_c + 8, bar_wqf = bar_wq + 8, bar_k = bar_wqf + 8;
    Scratch* sc = &g_scratch;
    if (warp == kConsumerWarps) {
        const char* kbase = (const char*)kc + ((size_t)pair * kSK + (kSK - kW) + split * 64) * (kDH * 2);
        uint64_t pol;
        asm volatile("createpolicy.fractional.L2::evict_first.b64 %0, 1.0;" : "=l"(pol));
        if (lane == 0) {
            asm volatile("prefetch.tensormap [%0];" ::"l"(&wq_map) : "memory");
            if (sbase & 1023u) __trap();
#pragma unroll
            for (int n = 0; n < kStart; n++) mbar_init(bar_full + n * 8, 1);
            mbar_init(bar_wq, 1);
            asm volatile("fence.mbarrier_init.release.cluster;" ::: "memory");
            mbar_expect_tx(bar_wq, 288 * 128);
#pragma unroll
            for (int h = 0; h < 2; h++)
                tma_2d(sbase + kOffRing + kWqSlot * kTileBytes + h * (144 * 128), &wq_map, j * 256 + (rank & 3) * 64,
                       (rank >> 2) * 288 + h * 144, bar_wq, pol);
#pragma unroll
            for (int n = 0; n < kStart; n++) {
                mbar_expect_tx(bar_full + n * 8, kTileBytes);
                bulk_g2s(sbase + kOffRing + n * kTileBytes, kbase + (size_t)n * (4 * kTileBytes), kTileBytes,
                         bar_full + n * 8, pol);
            }
#pragma unroll 1
            for (int n = kStart; n < kNumBars - 3; n++)
                mbar_init(bar_full + n * 8, n >= kNumFull + kTiles && n < kNumFull + kNumEmpty ? kConsumerWarps : 1);
            mbar_init(bar_wqf, kConsumerWarps);
            mbar_init(bar_k, kConsumerWarps);
            mbar_expect_tx(bar_qin, 2048);
            mbar_expect_tx(bar_ml, 128);
            mbar_expect_tx(bar_c, 8192);
            asm volatile("fence.mbarrier_init.release.cluster;" ::: "memory");
            asm volatile("prefetch.tensormap [%0];" ::"l"(&v_map) : "memory");
            asm volatile("prefetch.tensormap [%0];" ::"l"(&wo_map) : "memory");
            *(volatile uint32_t*)(smem + kOffMon) = 0xFFFFFFFFu;
            *(volatile uint32_t*)(smem + kOffMon + 8) = 0u;
        }
        __syncwarp();
        cluster_arrive();
        asm volatile("bar.arrive 2, 320;" ::: "memory");
        if (lane == 0) {
            const int vrow = pair * kSK + (kSK - kW) + split * 64 - kTiles * 256;
            int next = kStart;
            bool q_ready = false;
            int reported = 0;
#pragma unroll 1
            for (int m = 0; next < kItems; m++) {
                mbar_wait(bar_full + m * 8, 0);
                if (!q_ready) q_ready = mbar_test(bar_q, 0);
                int win = q_ready ? kInflight : kWin0;
                if (m < 2 * kTiles) {
                    asm volatile("red.relaxed.gpu.global.add.u32 [%0], 1;" ::"l"(&sc->landed) : "memory");
                    reported = m + 1;
                }
                if (q_ready) {
                    const unsigned long long gt = *(volatile unsigned long long*)(smem + kOffMon);
                    const uint32_t gl = (uint32_t)gt;
                    const int age = (int)(clock32() - (uint32_t)(gt >> 32));
                    const int lag = (int)gl + ((age * kBalRate) >> 10) + kBalBias - (m + 1) * 128;
                    if (gl != 0xFFFFFFFFu) win += (lag > kBalBehind2) ? 2 : (lag > kBalBehind1) ? 1 : (lag < -kBalAhead) ? -1 : 0;
                }
#pragma unroll 1
                while (next < kItems && ((next < 2 * kTiles ? next : 2 * kTiles + 1 + (next - 2 * kTiles) / 2) <= m + win ||
                                         m >= 2 * kTiles - 1)) {
                    const int n = next++;
                    const uint32_t bar = bar_full + n * 8;
                    if (n < 2 * kTiles) {
                        if (n >= kNSlot) mbar_wait(bar_empty + (n - kNSlot) * 8, 0);
                        else mbar_wait(bar_wqf, 0);
                        mbar_expect_tx(bar, kTileBytes);
                        const uint32_t dst = sbase + kOffRing + (n % kNSlot) * kTileBytes;
                        if (n < kTiles) bulk_g2s(dst, kbase + (size_t)n * (4 * kTileBytes), kTileBytes, bar, pol);
                        else tma_3d(dst, &v_map, 0, vrow + n * 256, 0, bar, pol);
                    } else {
                        const int part = n - 2 * kTiles;
                        mbar_wait(bar_empty + (26 + (part * (kWoBytes / kNWo)) / kTileBytes) * 8, 0);
                        mbar_wait(bar_empty + (26 + ((part + 1) * (kWoBytes / kNWo) - 1) / kTileBytes) * 8, 0);
                        mbar_expect_tx(bar_full + part * 8, kWoBytes / kNWo);
                        tma_3d(sbase + kOffRing + kWoSlot * kTileBytes + part * (kWoBytes / kNWo), &wo_map, rank * kWoCols,
                               part * kWoRows, 2 * j, bar_full + part * 8, pol);
                    }
                }
            }
            *(volatile uint32_t*)(smem + kOffMon + 8) = 1u;
            asm volatile("red.relaxed.gpu.global.add.u32 [%0], %1;" ::"l"(&sc->landed), "r"(2 * kTiles - reported) : "memory");
        }
        return;
    }
    cluster_arrive();
    if (warp == kConsumerWarps + 1) {
        if (cta == 0) {
#pragma unroll
            for (int i = 0; i < 2 * kD / 64; i++)
                asm volatile("st.relaxed.gpu.global.u32 [%0], %1;" ::"l"((uint32_t*)out + i * 32 + lane), "r"(0u) : "memory");
            __syncwarp();
        }
        asm volatile("bar.sync 2, 320;" ::: "memory");
        cluster_wait();
        const uint32_t epoch = *(volatile uint32_t*)(smem + kOffX + 1156);
        const uint32_t base = epoch * 4096u;
        if (cta == 0 && lane == 0)
            asm volatile("st.release.gpu.global.u32 [%0], %1;" ::"l"(&sc->cleared), "r"(epoch + 1u) : "memory");
        bool cleared = false;
        const int hd = lane >> 4;
        int state = 0;
        float Mc = 0.f;
        uint32_t it = 0;
        while (true) {
            if (lane == 0) {
                const uint32_t c0 = clock32();
                const uint32_t gl = ld_rlx_u32(&sc->landed) - base;
                uint32_t c1;
                asm volatile("{ .reg .u32 d; and.b32 d, %1, 0; mov.u32 %0, %clock; add.u32 %0, %0, d; }" : "=r"(c1) : "r"(gl) : "memory");
                *(volatile unsigned long long*)(smem + kOffMon) = ((unsigned long long)(c0 + ((c1 - c0) >> 1)) << 32) | gl;
            }
            if (state == 0 && __all_sync(0xffffffffu, mbar_test(bar_k, 0))) {
                const float2 v = *((const float2*)(smem + kOffML) + (lane & 15) * 2 + hd);
                float M = v.x;
#pragma unroll
                for (int o = 1; o < 16; o <<= 1) M = fmaxf(M, __shfl_xor_sync(0xffffffffu, M, o));
                float L = v.y * ex2(v.x - M);
#pragma unroll
                for (int o = 1; o < 16; o <<= 1) L += __shfl_xor_sync(0xffffffffu, L, o);
                Mc = M;
                if ((lane & 15) < 8)
                    st_async_u64(mapa(sbase + kOffML + 272 + (rank * 2 + hd) * 8, lane & 7),
                                 ((uint64_t)__float_as_uint(L) << 32) | __float_as_uint(M), mapa(bar_ml, lane & 7));
                state = 1;
            }
            if (!cleared) {
                uint32_t f = 0;
                if (lane == 0) asm volatile("ld.acquire.gpu.global.u32 %0, [%1];" : "=r"(f) : "l"(&sc->cleared) : "memory");
                cleared = __shfl_sync(0xffffffffu, f, 0) == epoch + 1u;
            }
            if (state == 1 && cleared && __all_sync(0xffffffffu, mbar_test(bar_ml, 0))) {
                const uint64_t w = *(const uint64_t*)(smem + kOffML + 272 + ((b * 4 + (lane & 3)) * 2 + hd) * 8);
                const float Mi = __uint_as_float((uint32_t)w), Li = __uint_as_float((uint32_t)(w >> 32));
                float Mg = fmaxf(Mi, __shfl_xor_sync(0xffffffffu, Mi, 1));
                Mg = fmaxf(Mg, __shfl_xor_sync(0xffffffffu, Mg, 2));
                float Lg = Li * ex2(Mi - Mg);
                Lg += __shfl_xor_sync(0xffffffffu, Lg, 1);
                Lg += __shfl_xor_sync(0xffffffffu, Lg, 2);
                if ((lane & 15) == 0) *((float*)(smem + kOffML + 256) + hd) = ex2(Mc - Mg) / Lg;
                __syncwarp();
                if (lane == 0) mbar_arrive(bar_stat);
                state = 2;
            }
            if (state == 2 && __any_sync(0xffffffffu, *(volatile uint32_t*)(smem + kOffMon + 8) != 0u)) break;
            if (++it > kSpinLimit) SPIN_FAIL();
        }
        return;
    }
    unsigned char* const wscr = smem + kOffA + warp * 1024;
    {
        uint4 wv[9];
        uint32_t xb[9];
        if (tid < 72) {
            const int bb = tid >= 36 ? 1 : 0;
            *(uint4*)(smem + kOffX + tid * 16) =
                ldg_stream128((const uint4*)(x + bb * kD + (rank >> 2) * 288) + (tid - bb * 36));
        } else if (tid == 96) {
            const uint32_t ep = ld_rlx_u32(&sc->landed) >> 12;
            *(uint32_t*)(smem + kOffX + 1156) = ep;
        }
        asm volatile("bar.sync 2, 320;" ::: "memory");
        {
            const unsigned short* xs = (const unsigned short*)(smem + kOffX) + ((g >> 1) & 1) * 288 + warp * 36;
#pragma unroll
            for (int i = 0; i < 8; i++) xb[i] = xs[2 * t + (i & 1) + 8 * (i >> 1)];
            xb[8] = xs[32 + t];
        }
        mbar_wait(bar_wq, 0);
#pragma unroll
        for (int i = 0; i < 9; i++) {
            const int r = warp * 36 + (i < 8 ? 2 * t + (i & 1) + 8 * (i >> 1) : 32 + t);
            wv[i] = lds128(sbase + kOffRing + kWqSlot * kTileBytes + r * 128 + ((g ^ (r & 7)) * 16));
        }
        float qa[4], qb[4];
        const int sh = (g & 1) * 16;
#pragma unroll
        for (int i = 0; i < 9; i++) xb[i] <<= sh;
        mma_bf16_z(qa, wv[0].x, wv[0].z, wv[1].x, wv[1].z, xb[0], xb[1]);
        mma_bf16_z(qb, wv[0].y, wv[0].w, wv[1].y, wv[1].w, xb[0], xb[1]);
#pragma unroll
        for (int u = 1; u < 4; u++) {
            mma_bf16(qa, wv[2 * u].x, wv[2 * u].z, wv[2 * u + 1].x, wv[2 * u + 1].z, xb[2 * u], xb[2 * u + 1]);
            mma_bf16(qb, wv[2 * u].y, wv[2 * u].w, wv[2 * u + 1].y, wv[2 * u + 1].w, xb[2 * u], xb[2 * u + 1]);
        }
        mma_bf16(qa, wv[8].x, wv[8].z, 0u, 0u, xb[8], 0u);
        mma_bf16(qb, wv[8].y, wv[8].w, 0u, 0u, xb[8], 0u);
        __syncwarp();
        if (lane == 0) mbar_arrive(bar_wqf);
        if (t < 2) {
            float4* dst = (float4*)(wscr + 512 + t * 256 + g * 32);
            dst[0] = make_float4(qa[0], qa[1], qb[0], qb[1]);
            dst[1] = make_float4(qa[2], qa[3], qb[2], qb[3]);
        }
        bar_consumers();
        cluster_wait();
        if (tid < 128) {
            const float* pp = (const float*)(smem + kOffA + 512) + tid;
            float s0 = 0.f;
#pragma unroll
            for (int w = 0; w < 8; w++) s0 += pp[w * 256];
            const uint32_t dst = sbase + kOffQin + ((rank >> 2) * 256 + (rank & 3) * 64 + (tid & 63)) * 4;
            const int r0 = (tid >> 6) * 4;
#pragma unroll
            for (int s = 0; s < 4; s++) st_async_u32(mapa(dst, r0 + s), __float_as_uint(s0), mapa(bar_qin, r0 + s));
        }
        mbar_wait(bar_qin, 0);
        {
            const float* qi = (const float*)(smem + kOffQin) + tid;
            ((__nv_bfloat16*)(smem + kOffQ))[tid] = __float2bfloat16(qi[0] + qi[256]);
        }
        bar_consumers();
        if (tid == 0) mbar_arrive(bar_q);
    }
    uint4 qf[4];
#pragma unroll
    for (int i = 0; i < 4; i++)
        qf[i] = lds128(sbase + kOffQ + (g & 1) * 256 + (4 * (i ^ ((g >> 1) & 1)) + t) * 16);

#pragma unroll 1
    for (int h = 0; h < 2; h++) {
        const int n = warp + 8 * h;
        mbar_wait(bar_full + n * 8, 0);
        const uint32_t kb = sbase + kOffRing + (n % kNSlot) * kTileBytes + g * 512 + t * 16;
        float s[4][4];
#pragma unroll
        for (int mt = 0; mt < 4; mt++) {
#pragma unroll
            for (int i = 0; i < 4; i++) {
                const uint32_t addr = kb + mt * 4096 + ((i ^ (g & 1)) * 64);
                const uint4 ra = lds128(addr), rb = lds128(addr + 256);
                if (i == 0) mma_bf16_z(s[mt], ra.x, rb.x, ra.y, rb.y, qf[i].x, qf[i].y);
                else mma_bf16(s[mt], ra.x, rb.x, ra.y, rb.y, qf[i].x, qf[i].y);
                mma_bf16(s[mt], ra.z, rb.z, ra.w, rb.w, qf[i].z, qf[i].w);
            }
        }
        __syncwarp();
        if (lane == 0) mbar_arrive(bar_empty + n * 8);
        const bool valid = ((t ^ g) & 1) == 0;
        const bool hi = t >= 2;
        float e0[4], e1[4];
        float m = -INFINITY;
#pragma unroll
        for (int i = 0; i < 4; i++) {
            e0[i] = valid ? (hi ? s[i][1] : s[i][0]) : -INFINITY;
            e1[i] = valid ? (hi ? s[i][3] : s[i][2]) : -INFINITY;
            uint32_t r = pack_bf16(e0[i], e1[i]);
            r = pack_bf16(__uint_as_float(r << 16) * kScale, __uint_as_float(r & 0xFFFF0000u) * kScale);
            e0[i] = __uint_as_float(r << 16);
            e1[i] = __uint_as_float(r & 0xFFFF0000u);
            m = fmaxf(m, fmaxf(e0[i], e1[i]));
        }
        m = fmaxf(m, __shfl_xor_sync(0xffffffffu, m, 1));
        m = fmaxf(m, __shfl_xor_sync(0xffffffffu, m, 4));
        m = fmaxf(m, __shfl_xor_sync(0xffffffffu, m, 8));
        m = fmaxf(m, __shfl_xor_sync(0xffffffffu, m, 16));
        const float mw = m * kLog2e;
        float l = 0.f;
        uint32_t* ps = (uint32_t*)(wscr + h * 256) + (t >> 1) * 32 + (g & 3) * 8 + (g >> 2);
#pragma unroll
        for (int i = 0; i < 4; i++) {
            const float p0 = ex2(fmaf(e0[i], kLog2e, -mw)), p1 = ex2(fmaf(e1[i], kLog2e, -mw));
            l += p0 + p1;
            if (valid) ps[2 * i] = pack_bf16(p0, p1);
        }
        l += __shfl_xor_sync(0xffffffffu, l, 1);
        l += __shfl_xor_sync(0xffffffffu, l, 4);
        l += __shfl_xor_sync(0xffffffffu, l, 8);
        l += __shfl_xor_sync(0xffffffffu, l, 16);
        if (lane == 0 || lane == 2) *((float2*)(smem + kOffML) + n * 2 + (t >> 1)) = make_float2(mw, l);
    }
    __syncwarp();
    if (lane == 0) mbar_arrive(bar_k);

    uint32_t cbase = sbase + kOffC + tid * 4;
    uint32_t csend0, csend1, cbar0, cbar1;
    {
        const uint32_t a = sbase + kOffC + rank * 1024 + (warp * 8 + g) * 16;
        csend0 = mapa(a, 2 * t); csend1 = mapa(a, 2 * t + 1);
        cbar0 = mapa(bar_c, 2 * t); cbar1 = mapa(bar_c, 2 * t + 1);
    }
    uint32_t odst16 = sbase + kOffA + (g >> 1) * 144 + (((t & 1) * 8 + warp) * 2 + (t >> 1)) * 4 + (g & 1) * 2;
    uint32_t osrc = sbase + kOffA + (g & 1) * 576 + t * 144;
    uint32_t wbase = sbase + kOffRing + kWoSlot * kTileBytes + ((lane & 7) + ((lane >> 4) & 1) * 8) * (kWoCols * 2) +
                     ((lane >> 3) & 1) * 16 + warp * 32;
    uint32_t* odst = (uint32_t*)(out + (t & 1) * kD + rank * kWoCols + warp * 16 + (t >> 1) * 8) + (g >> 1);
    pin(cbase); pin(csend0); pin(csend1); pin(cbar0); pin(cbar1); pin(wbase); pin(odst16); pin(osrc);
    pin(odst);

    float o[4] = {0.f, 0.f, 0.f, 0.f};
    {
        float2 gsc = make_float2(0.f, 0.f);
        const uint32_t pa = sbase + kOffA + (g & 1) * 128 + t * 32;
        const uint32_t va = sbase + kOffRing + (warp >> 2) * 8192 + ((lane & 7) + ((lane >> 4) & 1) * 8) * 128 +
                            ((((warp & 3) * 2 + ((lane >> 3) & 1)) ^ (lane & 7)) * 16);
        int slot = kTiles % kNSlot;
        mbar_wait(bar_k, 0);
        float fl;
        {
            const float mt = ldsf(sbase + kOffML + (lane & 15) * 16 + (lane >> 4) * 8);
            float M = mt;
#pragma unroll
            for (int o = 1; o < 16; o <<= 1) M = fmaxf(M, __shfl_xor_sync(0xffffffffu, M, o));
            fl = ex2(mt - M);
        }
#pragma unroll 1
        for (int tau = 0; tau < kTiles; tau++) {
            const uint32_t pw = pa + (tau & 7) * 1024 + (tau >> 3) * 256;
            const uint4 pA = lds128(pw), pB = lds128(pw + 16);
            const float f0 = __shfl_sync(0xffffffffu, fl, tau), f1 = __shfl_sync(0xffffffffu, fl, 16 + tau);
            if (tau == 12) {
                mbar_wait(bar_stat, 0);
                gsc = *(const float2*)(smem + kOffML + 256);
            }
            const uint32_t addr = va + slot * kTileBytes;
            slot = slot == kNSlot - 1 ? 0 : slot + 1;
            mbar_wait(bar_full + (kTiles + tau) * 8, 0);
            const uint4 v0 = ldsm_x4_trans(addr), v1 = ldsm_x4_trans(addr + 2048);
            const uint4 v2 = ldsm_x4_trans(addr + 4096), v3 = ldsm_x4_trans(addr + 6144);
            float a0[4], a1[4];
            mma_bf16_z(a0, v0.x, v0.y, v0.z, v0.w, pA.x, pA.y);
            mma_bf16_z(a1, v1.x, v1.y, v1.z, v1.w, pA.z, pA.w);
            mma_bf16(a0, v2.x, v2.y, v2.z, v2.w, pB.x, pB.y);
            mma_bf16(a1, v3.x, v3.y, v3.z, v3.w, pB.z, pB.w);
            __syncwarp();
            if (lane == 0 && kTiles + tau < kNumEmpty) mbar_arrive(bar_empty + (kTiles + tau) * 8);
            o[0] = fmaf(f0, a0[0] + a1[0], o[0]);
            o[1] = fmaf(f1, a0[1] + a1[1], o[1]);
            o[2] = fmaf(f0, a0[2] + a1[2], o[2]);
            o[3] = fmaf(f1, a0[3] + a1[3], o[3]);
        }
        const float y0 = o[0] * gsc.x, y1 = o[1] * gsc.y, y2 = o[2] * gsc.x, y3 = o[3] * gsc.y;
        st_async_v4(csend0, y0, y1, y2, y3, cbar0);
        st_async_v4(csend1, y0, y1, y2, y3, cbar1);
    }

    {
        mbar_wait(bar_c, 0);
        {
            float a[8];
#pragma unroll
            for (int r = 0; r < 8; r++) a[r] = ldsf(cbase + r * 1024);
            const uint32_t w = pack_bf16((a[0] + a[1]) + (a[2] + a[3]), (a[4] + a[5]) + (a[6] + a[7]));
            asm volatile("st.shared.u16 [%0], %1;" ::"r"(odst16), "h"((unsigned short)w) : "memory");
            asm volatile("st.shared.u16 [%0], %1;" ::"r"(odst16 + 576), "h"((unsigned short)(w >> 16)) : "memory");
        }
        bar_consumers();
        if (warp < 5) {
            uint4 bq[8];
#pragma unroll
            for (int i = 0; i < 8; i++) bq[i] = lds128(osrc + i * 16);
            float acc0[4] = {0.f, 0.f, 0.f, 0.f}, acc1[4] = {0.f, 0.f, 0.f, 0.f};
#pragma unroll
            for (int pp = 0; pp < 2; pp++) {
                uint4 wa[2][2][2];
#pragma unroll
                for (int q = 0; q < 2; q++) {
                    mbar_wait(bar_full + (2 * pp + q) * 8, 1);
#pragma unroll
                    for (int h = 0; h < 2; h++)
#pragma unroll
                        for (int blk = 0; blk < 2; blk++)
                            wa[q][h][blk] = ldsm_x4_trans(wbase + (2 * pp + q) * (kWoBytes / kNWo) +
                                                          (h * kWoRows + blk * 16) * (kWoCols * 2));
                }
#pragma unroll
                for (int q = 0; q < 2; q++)
#pragma unroll
                    for (int h = 0; h < 2; h++) {
                        const uint4 bb = bq[h * 4 + 2 * pp + q];
                        mma_bf16(acc0, wa[q][h][0].x, wa[q][h][0].y, wa[q][h][0].z, wa[q][h][0].w, bb.x, bb.y);
                        mma_bf16(acc1, wa[q][h][1].x, wa[q][h][1].y, wa[q][h][1].z, wa[q][h][1].w, bb.z, bb.w);
                    }
            }
            const float lo = (t & 1) ? acc0[1] + acc1[1] : acc0[0] + acc1[0];
            const float hi = (t & 1) ? acc0[3] + acc1[3] : acc0[2] + acc1[2];
            const float v = (t & 2) ? hi : lo;
            const uint32_t w = (g & 1) ? pack_bf16(-0.f, v) : pack_bf16(v, -0.f);
            if (warp < 4 || t < 2)
                asm volatile("red.relaxed.gpu.global.add.noftz.bf16x2 [%0], %1;" ::"l"(odst), "r"(w) : "memory");
        }
    }
}

}

typedef CUresult (*EncodeTiledFn)(CUtensorMap*, CUtensorMapDataType, cuuint32_t, void*, const cuuint64_t*,
                                  const cuuint64_t*, const cuuint32_t*, const cuuint32_t*, CUtensorMapInterleave,
                                  CUtensorMapSwizzle, CUtensorMapL2promotion, CUtensorMapFloatOOBfill);

extern "C" void kernel_launch(void* const* d_in, const int* in_sizes, int n_in, void* d_out, int out_size) {
    (void)in_sizes; (void)n_in; (void)out_size;
    static EncodeTiledFn encode = nullptr;
    if (!encode) {
        void* fn = nullptr;
        cudaDriverEntryPointQueryResult st;
        cudaGetDriverEntryPoint("cuTensorMapEncodeTiled", &fn, cudaEnableDefault, &st);
        encode = (EncodeTiledFn)fn;
        cudaFuncSetAttribute(decode_attn_kernel, cudaFuncAttributeMaxDynamicSharedMemorySize, kSmemBytes);
    }
    CUtensorMap wq_map, v_map, wo_map;
    const cuuint32_t estr[3] = {1, 1, 1};
    {
        const cuuint64_t dims[2] = {4096, (cuuint64_t)kD};
        const cuuint64_t strides[1] = {4096 * 2};
        const cuuint32_t box[2] = {64, 144};
        encode(&wq_map, CU_TENSOR_MAP_DATA_TYPE_BFLOAT16, 2, d_in[3], dims, strides, box, estr,
               CU_TENSOR_MAP_INTERLEAVE_NONE, CU_TENSOR_MAP_SWIZZLE_128B, CU_TENSOR_MAP_L2_PROMOTION_L2_128B,
               CU_TENSOR_MAP_FLOAT_OOB_FILL_NONE);
    }
    {
        const cuuint64_t dims[3] = {64, (cuuint64_t)2 * 16 * kSK, 2};
        const cuuint64_t strides[2] = {kDH * 2, 128};
        const cuuint32_t box[3] = {64, 64, 2};
        encode(&v_map, CU_TENSOR_MAP_DATA_TYPE_BFLOAT16, 3, d_in[2], dims, strides, box, estr,
               CU_TENSOR_MAP_INTERLEAVE_NONE, CU_TENSOR_MAP_SWIZZLE_128B, CU_TENSOR_MAP_L2_PROMOTION_L2_256B,
               CU_TENSOR_MAP_FLOAT_OOB_FILL_NONE);
    }
    {
        const cuuint64_t dims[3] = {(cuuint64_t)kD, 128, 32};
        const cuuint64_t strides[2] = {(cuuint64_t)kD * 2, (cuuint64_t)kD * 2 * 128};
        const cuuint32_t box[3] = {(cuuint32_t)kWoCols, (cuuint32_t)kWoRows, 2};
        encode(&wo_map, CU_TENSOR_MAP_DATA_TYPE_BFLOAT16, 3, d_in[4], dims, strides, box, estr,
               CU_TENSOR_MAP_INTERLEAVE_NONE, CU_TENSOR_MAP_SWIZZLE_NONE, CU_TENSOR_MAP_L2_PROMOTION_L2_256B,
               CU_TENSOR_MAP_FLOAT_OOB_FILL_NONE);
    }
    decode_attn_kernel<<<kNCTA, kThreads, kSmemBytes, cudaStreamPerThread>>>(
        (const __nv_bfloat16*)d_in[0], (const __nv_bfloat16*)d_in[1], (__nv_bfloat16*)d_out, wq_map, v_map, wo_map);
}
```
